```python
import torch

def _softmax(x, axis=-1):
    return torch.softmax(x, dim=axis)
def _gelu(x):
    return torch.nn.functional.gelu(x, approximate="tanh")
def _silu(x):
    return torch.nn.functional.silu(x)
def _sigmoid(x):
    return torch.sigmoid(x)
def _layernorm(x, axis=-1, eps=1e-5):
    m = x.mean(dim=axis, keepdim=True)
    v = x.var(dim=axis, keepdim=True, unbiased=False)
    return (x - m) / torch.sqrt(v + eps)
def _scatter_add(tgt, idx, src, axis=0):
    return tgt.clone().index_add_(axis, idx, src)
def _segment_sum(src, seg, n):
    out = torch.zeros((n,) + src.shape[1:], dtype=src.dtype)
    return out.index_add_(0, seg, src)
def _pad(x, pw):
    flat = tuple(v for pair in reversed(pw) for v in pair)
    return torch.nn.functional.pad(x, flat)

kernel_name = 'recurrent_scan__compressed_kv_cla__glu_gated_geglu__prompt'

def setup_inputs():

    _w = (lambda a: (lambda t: t.to(torch.bfloat16) if t.is_floating_point() else t)(torch.as_tensor(a)))
    def _A_setup():
        B, H, Sq, Sk, D, M = 1, 32, 2048, 2048, 128, 512
        Dc = 4 * D
        return {
            "x": _w((lambda *s: torch.randn(*s, dtype=torch.bfloat16) * 0.05)(B, Sq, M)),
            "c_kv": _w((lambda *s: torch.randn(*s, dtype=torch.bfloat16) * 1.6)(B, Sk, Dc)),
            "w_q": _w((lambda *s: torch.randn(*s, dtype=torch.bfloat16) * 1.6)(M, H, D) * (M ** -0.5)),
            "w_uk": _w((lambda *s: torch.randn(*s, dtype=torch.bfloat16) * 1.6)(Dc, H, D) * (Dc ** -0.5)),
            "w_uv": _w((lambda *s: torch.randn(*s, dtype=torch.bfloat16) * 1.6)(Dc, H, D) * (Dc ** -0.5)),
            "w_o": _w((lambda *s: torch.randn(*s, dtype=torch.bfloat16) * 1.6)(H, D, M) * ((H * D) ** -0.5)),
        }
    _A_in = _A_setup()

    def _B_setup():
        B, S, Dm, Df = 1, 2048, 512, 1792
        return {
            "x": _w((lambda *s: torch.randn(*s, dtype=torch.bfloat16) * 0.05)(B, S, Dm)),
            "w_gate": _w((lambda *s: torch.randn(*s, dtype=torch.bfloat16) * 0.2)(Dm, Df) * (Dm ** -0.5)),
            "w_up": _w((lambda *s: torch.randn(*s, dtype=torch.bfloat16) * 0.2)(Dm, Df) * (Dm ** -0.5)),
            "w_down": _w((lambda *s: torch.randn(*s, dtype=torch.bfloat16) * 0.2)(Df, Dm) * (Df ** -0.5)),
        }
    _B_in = _B_setup()

    return {
        "A_x": _A_in["x"],
        "A_c_kv": _A_in["c_kv"],
        "A_w_q": _A_in["w_q"],
        "A_w_uk": _A_in["w_uk"],
        "A_w_uv": _A_in["w_uv"],
        "A_w_o": _A_in["w_o"],
        "B_x": _B_in["x"],
        "B_w_gate": _B_in["w_gate"],
        "B_w_up": _B_in["w_up"],
        "B_w_down": _B_in["w_down"],
    }

def reference(A_x, A_c_kv, A_w_q, A_w_uk, A_w_uv, A_w_o, B_x, B_w_gate, B_w_up, B_w_down):
    def _A_ref(x, c_kv, w_q, w_uk, w_uv, w_o):
        B, Sq, M = x.shape[0], x.shape[1], x.shape[2]
        Sk = c_kv.shape[1]
        H, D = w_q.shape[1], w_q.shape[2]
        q = torch.einsum("bqm,mhd->bhqd", x, w_q)
        k = torch.einsum("bkc,chd->bhkd", c_kv, w_uk)
        v = torch.einsum("bkc,chd->bhkd", c_kv, w_uv)
        scores = torch.einsum("bhqd,bhkd->bhqk", q, k) * (D ** -0.5)
        off = Sk - Sq
        qi = torch.arange(Sq)[:, None]
        kj = torch.arange(Sk)[None, :]
        cmask = kj <= (qi + off)
        scores = torch.where(cmask[None, None], scores, -1e9)
        p = _softmax(scores, axis=-1)
        ctx = torch.einsum("bhqk,bhkd->bhqd", p, v)
        return torch.einsum("bhqd,hdm->bqm", ctx, w_o)

    def _B_ref(x, w_gate, w_up, w_down):
        g = torch.einsum("bsd,df->bsf", x, w_gate)
        u = torch.einsum("bsd,df->bsf", x, w_up)
        h = _gelu(g) * u
        return torch.einsum("bsf,fd->bsd", h, w_down)

    x = A_x
    xn = _layernorm(x, axis=-1)
    s = _A_ref(xn, A_c_kv, A_w_q, A_w_uk, A_w_uv, A_w_o)
    g = _silu(_B_ref(xn, B_w_gate, B_w_up, B_w_down))
    return x + s * g
```

```cpp
#include <cuda_runtime.h>
#include <cuda_bf16.h>
#include <cuda.h>
#include <stdint.h>
#include <string.h>

typedef __nv_bfloat16 bf16;

template<int TB>
__device__ __forceinline__ void wgmma_ss_n256(float (&d)[128], uint64_t da, uint64_t db, int scale_d) {
  asm volatile("{\n.reg .pred p;\nsetp.ne.b32 p, %130, 0;\n"
    "wgmma.mma_async.sync.aligned.m64n256k16.f32.bf16.bf16 {%0, %1, %2, %3, %4, %5, %6, %7, %8, %9, %10, %11, %12, %13, %14, %15, %16, %17, %18, %19, %20, %21, %22, %23, %24, %25, %26, %27, %28, %29, %30, %31, %32, %33, %34, %35, %36, %37, %38, %39, %40, %41, %42, %43, %44, %45, %46, %47, %48, %49, %50, %51, %52, %53, %54, %55, %56, %57, %58, %59, %60, %61, %62, %63, %64, %65, %66, %67, %68, %69, %70, %71, %72, %73, %74, %75, %76, %77, %78, %79, %80, %81, %82, %83, %84, %85, %86, %87, %88, %89, %90, %91, %92, %93, %94, %95, %96, %97, %98, %99, %100, %101, %102, %103, %104, %105, %106, %107, %108, %109, %110, %111, %112, %113, %114, %115, %116, %117, %118, %119, %120, %121, %122, %123, %124, %125, %126, %127}, %128, %129, p, 1, 1, 0, %131;\n}\n"
    : "+f"(d[0]), "+f"(d[1]), "+f"(d[2]), "+f"(d[3]), "+f"(d[4]), "+f"(d[5]), "+f"(d[6]), "+f"(d[7]), "+f"(d[8]), "+f"(d[9]), "+f"(d[10]), "+f"(d[11]), "+f"(d[12]), "+f"(d[13]), "+f"(d[14]), "+f"(d[15]), "+f"(d[16]), "+f"(d[17]), "+f"(d[18]), "+f"(d[19]), "+f"(d[20]), "+f"(d[21]), "+f"(d[22]), "+f"(d[23]), "+f"(d[24]), "+f"(d[25]), "+f"(d[26]), "+f"(d[27]), "+f"(d[28]), "+f"(d[29]), "+f"(d[30]), "+f"(d[31]), "+f"(d[32]), "+f"(d[33]), "+f"(d[34]), "+f"(d[35]), "+f"(d[36]), "+f"(d[37]), "+f"(d[38]), "+f"(d[39]), "+f"(d[40]), "+f"(d[41]), "+f"(d[42]), "+f"(d[43]), "+f"(d[44]), "+f"(d[45]), "+f"(d[46]), "+f"(d[47]), "+f"(d[48]), "+f"(d[49]), "+f"(d[50]), "+f"(d[51]), "+f"(d[52]), "+f"(d[53]), "+f"(d[54]), "+f"(d[55]), "+f"(d[56]), "+f"(d[57]), "+f"(d[58]), "+f"(d[59]), "+f"(d[60]), "+f"(d[61]), "+f"(d[62]), "+f"(d[63]), "+f"(d[64]), "+f"(d[65]), "+f"(d[66]), "+f"(d[67]), "+f"(d[68]), "+f"(d[69]), "+f"(d[70]), "+f"(d[71]), "+f"(d[72]), "+f"(d[73]), "+f"(d[74]), "+f"(d[75]), "+f"(d[76]), "+f"(d[77]), "+f"(d[78]), "+f"(d[79]), "+f"(d[80]), "+f"(d[81]), "+f"(d[82]), "+f"(d[83]), "+f"(d[84]), "+f"(d[85]), "+f"(d[86]), "+f"(d[87]), "+f"(d[88]), "+f"(d[89]), "+f"(d[90]), "+f"(d[91]), "+f"(d[92]), "+f"(d[93]), "+f"(d[94]), "+f"(d[95]), "+f"(d[96]), "+f"(d[97]), "+f"(d[98]), "+f"(d[99]), "+f"(d[100]), "+f"(d[101]), "+f"(d[102]), "+f"(d[103]), "+f"(d[104]), "+f"(d[105]), "+f"(d[106]), "+f"(d[107]), "+f"(d[108]), "+f"(d[109]), "+f"(d[110]), "+f"(d[111]), "+f"(d[112]), "+f"(d[113]), "+f"(d[114]), "+f"(d[115]), "+f"(d[116]), "+f"(d[117]), "+f"(d[118]), "+f"(d[119]), "+f"(d[120]), "+f"(d[121]), "+f"(d[122]), "+f"(d[123]), "+f"(d[124]), "+f"(d[125]), "+f"(d[126]), "+f"(d[127])
    : "l"(da), "l"(db), "r"(scale_d), "n"(TB));
}

template<int TB>
__device__ __forceinline__ void wgmma_ss_n128(float (&d)[64], uint64_t da, uint64_t db, int scale_d) {
  asm volatile("{\n.reg .pred p;\nsetp.ne.b32 p, %66, 0;\n"
    "wgmma.mma_async.sync.aligned.m64n128k16.f32.bf16.bf16 {%0, %1, %2, %3, %4, %5, %6, %7, %8, %9, %10, %11, %12, %13, %14, %15, %16, %17, %18, %19, %20, %21, %22, %23, %24, %25, %26, %27, %28, %29, %30, %31, %32, %33, %34, %35, %36, %37, %38, %39, %40, %41, %42, %43, %44, %45, %46, %47, %48, %49, %50, %51, %52, %53, %54, %55, %56, %57, %58, %59, %60, %61, %62, %63}, %64, %65, p, 1, 1, 0, %67;\n}\n"
    : "+f"(d[0]), "+f"(d[1]), "+f"(d[2]), "+f"(d[3]), "+f"(d[4]), "+f"(d[5]), "+f"(d[6]), "+f"(d[7]), "+f"(d[8]), "+f"(d[9]), "+f"(d[10]), "+f"(d[11]), "+f"(d[12]), "+f"(d[13]), "+f"(d[14]), "+f"(d[15]), "+f"(d[16]), "+f"(d[17]), "+f"(d[18]), "+f"(d[19]), "+f"(d[20]), "+f"(d[21]), "+f"(d[22]), "+f"(d[23]), "+f"(d[24]), "+f"(d[25]), "+f"(d[26]), "+f"(d[27]), "+f"(d[28]), "+f"(d[29]), "+f"(d[30]), "+f"(d[31]), "+f"(d[32]), "+f"(d[33]), "+f"(d[34]), "+f"(d[35]), "+f"(d[36]), "+f"(d[37]), "+f"(d[38]), "+f"(d[39]), "+f"(d[40]), "+f"(d[41]), "+f"(d[42]), "+f"(d[43]), "+f"(d[44]), "+f"(d[45]), "+f"(d[46]), "+f"(d[47]), "+f"(d[48]), "+f"(d[49]), "+f"(d[50]), "+f"(d[51]), "+f"(d[52]), "+f"(d[53]), "+f"(d[54]), "+f"(d[55]), "+f"(d[56]), "+f"(d[57]), "+f"(d[58]), "+f"(d[59]), "+f"(d[60]), "+f"(d[61]), "+f"(d[62]), "+f"(d[63])
    : "l"(da), "l"(db), "r"(scale_d), "n"(TB));
}

template<int TB>
__device__ __forceinline__ void wgmma_rs_n128(float (&d)[64], uint32_t a0, uint32_t a1, uint32_t a2, uint32_t a3, uint64_t db, int scale_d) {
  asm volatile("{\n.reg .pred p;\nsetp.ne.b32 p, %69, 0;\n"
    "wgmma.mma_async.sync.aligned.m64n128k16.f32.bf16.bf16 {%0, %1, %2, %3, %4, %5, %6, %7, %8, %9, %10, %11, %12, %13, %14, %15, %16, %17, %18, %19, %20, %21, %22, %23, %24, %25, %26, %27, %28, %29, %30, %31, %32, %33, %34, %35, %36, %37, %38, %39, %40, %41, %42, %43, %44, %45, %46, %47, %48, %49, %50, %51, %52, %53, %54, %55, %56, %57, %58, %59, %60, %61, %62, %63}, {%64, %65, %66, %67}, %68, p, 1, 1, %70;\n}\n"
    : "+f"(d[0]), "+f"(d[1]), "+f"(d[2]), "+f"(d[3]), "+f"(d[4]), "+f"(d[5]), "+f"(d[6]), "+f"(d[7]), "+f"(d[8]), "+f"(d[9]), "+f"(d[10]), "+f"(d[11]), "+f"(d[12]), "+f"(d[13]), "+f"(d[14]), "+f"(d[15]), "+f"(d[16]), "+f"(d[17]), "+f"(d[18]), "+f"(d[19]), "+f"(d[20]), "+f"(d[21]), "+f"(d[22]), "+f"(d[23]), "+f"(d[24]), "+f"(d[25]), "+f"(d[26]), "+f"(d[27]), "+f"(d[28]), "+f"(d[29]), "+f"(d[30]), "+f"(d[31]), "+f"(d[32]), "+f"(d[33]), "+f"(d[34]), "+f"(d[35]), "+f"(d[36]), "+f"(d[37]), "+f"(d[38]), "+f"(d[39]), "+f"(d[40]), "+f"(d[41]), "+f"(d[42]), "+f"(d[43]), "+f"(d[44]), "+f"(d[45]), "+f"(d[46]), "+f"(d[47]), "+f"(d[48]), "+f"(d[49]), "+f"(d[50]), "+f"(d[51]), "+f"(d[52]), "+f"(d[53]), "+f"(d[54]), "+f"(d[55]), "+f"(d[56]), "+f"(d[57]), "+f"(d[58]), "+f"(d[59]), "+f"(d[60]), "+f"(d[61]), "+f"(d[62]), "+f"(d[63])
    : "r"(a0), "r"(a1), "r"(a2), "r"(a3), "l"(db), "r"(scale_d), "n"(TB));
}

template<int TB>
__device__ __forceinline__ void wgmma_rs_n64(float (&d)[32], uint32_t a0, uint32_t a1, uint32_t a2, uint32_t a3, uint64_t db, int scale_d) {
  asm volatile("{\n.reg .pred p;\nsetp.ne.b32 p, %37, 0;\n"
    "wgmma.mma_async.sync.aligned.m64n64k16.f32.bf16.bf16 {%0, %1, %2, %3, %4, %5, %6, %7, %8, %9, %10, %11, %12, %13, %14, %15, %16, %17, %18, %19, %20, %21, %22, %23, %24, %25, %26, %27, %28, %29, %30, %31}, {%32, %33, %34, %35}, %36, p, 1, 1, %38;\n}\n"
    : "+f"(d[0]), "+f"(d[1]), "+f"(d[2]), "+f"(d[3]), "+f"(d[4]), "+f"(d[5]), "+f"(d[6]), "+f"(d[7]), "+f"(d[8]), "+f"(d[9]), "+f"(d[10]), "+f"(d[11]), "+f"(d[12]), "+f"(d[13]), "+f"(d[14]), "+f"(d[15]), "+f"(d[16]), "+f"(d[17]), "+f"(d[18]), "+f"(d[19]), "+f"(d[20]), "+f"(d[21]), "+f"(d[22]), "+f"(d[23]), "+f"(d[24]), "+f"(d[25]), "+f"(d[26]), "+f"(d[27]), "+f"(d[28]), "+f"(d[29]), "+f"(d[30]), "+f"(d[31])
    : "r"(a0), "r"(a1), "r"(a2), "r"(a3), "l"(db), "r"(scale_d), "n"(TB));
}

template<int TB>
__device__ __forceinline__ void wgmma_ss_n64(float (&d)[32], uint64_t da, uint64_t db, int scale_d) {
  asm volatile("{\n.reg .pred p;\nsetp.ne.b32 p, %34, 0;\n"
    "wgmma.mma_async.sync.aligned.m64n64k16.f32.bf16.bf16 {%0, %1, %2, %3, %4, %5, %6, %7, %8, %9, %10, %11, %12, %13, %14, %15, %16, %17, %18, %19, %20, %21, %22, %23, %24, %25, %26, %27, %28, %29, %30, %31}, %32, %33, p, 1, 1, 0, %35;\n}\n"
    : "+f"(d[0]), "+f"(d[1]), "+f"(d[2]), "+f"(d[3]), "+f"(d[4]), "+f"(d[5]), "+f"(d[6]), "+f"(d[7]), "+f"(d[8]), "+f"(d[9]), "+f"(d[10]), "+f"(d[11]), "+f"(d[12]), "+f"(d[13]), "+f"(d[14]), "+f"(d[15]), "+f"(d[16]), "+f"(d[17]), "+f"(d[18]), "+f"(d[19]), "+f"(d[20]), "+f"(d[21]), "+f"(d[22]), "+f"(d[23]), "+f"(d[24]), "+f"(d[25]), "+f"(d[26]), "+f"(d[27]), "+f"(d[28]), "+f"(d[29]), "+f"(d[30]), "+f"(d[31])
    : "l"(da), "l"(db), "r"(scale_d), "n"(TB));
}

namespace mk {

constexpr int SEQ = 2048, DM = 512, NH = 32, DFF = 1792;
constexpr int NTHREADS = 384;

constexpr uint32_t RING_BYTES = 196608;
constexpr uint32_t STG_OFF = RING_BYTES;
constexpr uint32_t BAR_OFF = STG_OFF + 32768;
constexpr uint32_t B_FULLG = BAR_OFF;
constexpr uint32_t B_EMPTYG = B_FULLG + 32;
constexpr uint32_t B_FULLA = B_EMPTYG + 32;
constexpr uint32_t B_EMPTYA = B_FULLA + 48;
constexpr uint32_t B_STF = B_EMPTYA + 48;
constexpr uint32_t B_STE = B_STF + 32;
constexpr uint32_t B_DONE = B_STE + 32;
constexpr uint32_t MISC_OFF = B_DONE + 8;
constexpr uint32_t SMEM_BYTES = MISC_OFF + 64 + 1024;

enum { TM_XN = 0, TM_CKV, TM_H, TM_CTX, TM_WUK, TM_WUV, TM_WG, TM_WU, TM_WD, TM_WO, TM_WQ, TM_KVL,
       TM_KVS, TM_HS, TM_CTXS, TM_GS, TM_OUTS, TM_COUNT };

enum { IT_KV = 0, IT_GU = 1, IT_DN = 2, IT_OP = 3, IT_AT = 4 };
__host__ __device__ inline uint32_t mk_item(int type, int j, int idx, int k0, int nk, int flag, int np) {
  return (uint32_t)type | (j << 3) | (idx << 6) | (k0 << 11) | (nk << 17) | (flag << 24) | (np << 25);
}
constexpr int MAX_ITEMS = 1024;
constexpr int MAX_CL = 72;

struct Params {
  CUtensorMap tm[TM_COUNT];
  const bf16* x;
  bf16* out;
  uint16_t off[MAX_CL + 8];
  uint32_t items[MAX_ITEMS];
};

constexpr int F_LN = 0;
constexpr int F_KV = 32;
constexpr int F_H = F_KV + 512;
constexpr int F_CTX = F_H + 32;
constexpr int F_G = F_CTX + 512;
constexpr int F_PART = F_G + 64;
constexpr int F_START = F_PART + 256;
constexpr int F_COUNT = F_START + 32;

__device__ __align__(1024) bf16 g_xn[SEQ * DM];
__device__ __align__(1024) bf16 g_kv[SEQ * 8192];
__device__ __align__(1024) bf16 g_h[SEQ * DFF];
__device__ __align__(1024) bf16 g_ctx[SEQ * 4096];
__device__ __align__(1024) bf16 g_g[SEQ * DM];
__device__ __align__(1024) float g_part[SEQ * DM];
__device__ unsigned g_flags[F_COUNT];
__device__ unsigned g_epoch;

__device__ __forceinline__ uint32_t smem_u32(const void* p) { return (uint32_t)__cvta_generic_to_shared(p); }
__device__ __forceinline__ void mbar_init(uint32_t bar, int cnt) {
  asm volatile("mbarrier.init.shared::cta.b64 [%0], %1;" ::"r"(bar), "r"(cnt));
}
__device__ __forceinline__ void mbar_expect_tx(uint32_t bar, uint32_t bytes) {
  asm volatile("mbarrier.arrive.expect_tx.shared::cta.b64 _, [%0], %1;" ::"r"(bar), "r"(bytes) : "memory");
}
__device__ __forceinline__ void mbar_arrive(uint32_t bar) {
  asm volatile("mbarrier.arrive.shared::cta.b64 _, [%0];" ::"r"(bar) : "memory");
}
__device__ __forceinline__ void mbar_arrive_cta(uint32_t bar, uint32_t cta) {
  asm volatile("{\n.reg .b32 ra;\nmapa.shared::cluster.u32 ra, %0, %1;\nmbarrier.arrive.shared::cluster.b64 _, [ra];\n}"
               ::"r"(bar), "r"(cta) : "memory");
}
__device__ __forceinline__ bool mbar_try(uint32_t bar, uint32_t parity) {
  uint32_t ok;
  asm volatile("{\n.reg .pred p;\nmbarrier.try_wait.parity.shared::cta.b64 p, [%1], %2;\nselp.u32 %0, 1, 0, p;\n}"
               : "=r"(ok) : "r"(bar), "r"(parity) : "memory");
  return ok != 0;
}
__device__ __forceinline__ uint32_t clk32() {
  uint32_t t;
  asm volatile("mov.u32 %0, %%clock;" : "=r"(t));
  return t;
}
__device__ __forceinline__ void spin_guard(uint32_t t0) {
  asm volatile("{\n.reg .pred p;\n.reg .s32 d;\nmov.u32 d, %%clock;\nsub.s32 d, d, %0;\nsetp.lt.s32 p, d, 0;\n@p st.global.u32 [%1], %0;\n}"
               ::"r"(t0), "l"(0ull) : "memory");
}
__device__ __forceinline__ void mbar_wait(uint32_t bar, uint32_t parity) {
  if (mbar_try(bar, parity)) return;
  const uint32_t t0 = clk32();
  while (!mbar_try(bar, parity)) spin_guard(t0);
}
__device__ __forceinline__ void tma_load_2d(uint32_t dst, const CUtensorMap* m, uint32_t bar, int c0, int c1) {
  asm volatile("cp.async.bulk.tensor.2d.shared::cluster.global.mbarrier::complete_tx::bytes [%0], [%1, {%3, %4}], [%2];"
               ::"r"(dst), "l"(m), "r"(bar), "r"(c0), "r"(c1) : "memory");
}
__device__ __forceinline__ void tma_load_2d_mc(uint32_t dst, const CUtensorMap* m, uint32_t bar, int c0, int c1) {
  asm volatile("cp.async.bulk.tensor.2d.shared::cluster.global.mbarrier::complete_tx::bytes.multicast::cluster [%0], [%1, {%3, %4}], [%2], %5;"
               ::"r"(dst), "l"(m), "r"(bar), "r"(c0), "r"(c1), "h"((uint16_t)3) : "memory");
}
__device__ __forceinline__ void tma_load_3d_mc(uint32_t dst, const CUtensorMap* m, uint32_t bar, int c0, int c1, int c2) {
  asm volatile("cp.async.bulk.tensor.3d.shared::cluster.global.mbarrier::complete_tx::bytes.multicast::cluster [%0], [%1, {%3, %4, %5}], [%2], %6;"
               ::"r"(dst), "l"(m), "r"(bar), "r"(c0), "r"(c1), "r"(c2), "h"((uint16_t)3) : "memory");
}
__device__ __forceinline__ void tma_store_2d(const CUtensorMap* m, uint32_t src, int c0, int c1) {
  asm volatile("cp.async.bulk.tensor.2d.global.shared::cta.bulk_group [%0, {%2, %3}], [%1];"
               ::"l"(m), "r"(src), "r"(c0), "r"(c1) : "memory");
}
__device__ __forceinline__ unsigned ld_acquire(const unsigned* p) {
  unsigned v;
  asm volatile("ld.acquire.gpu.global.u32 %0, [%1];" : "=r"(v) : "l"(p) : "memory");
  return v;
}
__device__ __forceinline__ void red_release(unsigned* p) {
  asm volatile("red.release.gpu.global.add.u32 [%0], 1;" ::"l"(p) : "memory");
}
__device__ __forceinline__ void wait_flag(const unsigned* p, unsigned target) {
  const uint32_t t0 = clk32();
  while ((int)(ld_acquire(p) - target) < 0) {
    __nanosleep(40);
    spin_guard(t0);
  }
}
__device__ __forceinline__ uint64_t mkdesc(uint32_t addr, uint32_t lbo, uint32_t sbo) {
  return (uint64_t)((addr & 0x3FFFF) >> 4) | ((uint64_t)(lbo >> 4) << 16) | ((uint64_t)(sbo >> 4) << 32) | (1ull << 62);
}
#define WG_FENCE() asm volatile("wgmma.fence.sync.aligned;" ::: "memory")
#define WG_COMMIT() asm volatile("wgmma.commit_group.sync.aligned;" ::: "memory")
#define WG_WAIT(n) asm volatile("wgmma.wait_group.sync.aligned %0;" ::"n"(n) : "memory")
template <int N> __device__ __forceinline__ void fence_regs(float (&r)[N]) {
#pragma unroll
  for (int i = 0; i < N; i++) asm volatile("" : "+f"(r[i])::"memory");
}
template <int N> __device__ __forceinline__ void fence_regs(uint32_t (&r)[N]) {
#pragma unroll
  for (int i = 0; i < N; i++) asm volatile("" : "+r"(r[i])::"memory");
}
__device__ __forceinline__ uint32_t pack_bf16(float lo, float hi) {
  uint32_t r;
  asm("cvt.rn.bf16x2.f32 %0, %1, %2;" : "=r"(r) : "f"(hi), "f"(lo));
  return r;
}
__device__ __forceinline__ float round_bf16(float v) { return __bfloat162float(__float2bfloat16_rn(v)); }
__device__ __forceinline__ float ex2(float x) {
  float y;
  asm("ex2.approx.ftz.f32 %0, %1;" : "=f"(y) : "f"(x));
  return y;
}
__device__ __forceinline__ void stsm_x4(uint32_t addr, uint32_t a, uint32_t b, uint32_t c, uint32_t d) {
  asm volatile("stmatrix.sync.aligned.m8n8.x4.shared.b16 [%0], {%1, %2, %3, %4};" ::"r"(addr), "r"(a), "r"(b), "r"(c), "r"(d) : "memory");
}
__device__ __forceinline__ void bar_sync(int id, int n) { asm volatile("bar.sync %0, %1;" ::"r"(id), "r"(n) : "memory"); }
__device__ __forceinline__ void bar_arrive(int id, int n) { asm volatile("bar.arrive %0, %1;" ::"r"(id), "r"(n) : "memory"); }
__device__ __forceinline__ void cluster_sync() {
  asm volatile("barrier.cluster.arrive.aligned;\nbarrier.cluster.wait.aligned;" ::: "memory");
}

struct Ring {
  uint32_t gs, as;
  uint32_t gph, aph;
  uint32_t mode;
  __device__ __forceinline__ void to_g() {
    if (mode != 0) { mode = 0; gs = (0x032210u >> (as * 4)) & 3; }
  }
  __device__ __forceinline__ void to_a() {
    if (mode != 1) { mode = 1; as = (0x5320u >> (gs * 4)) & 7; }
  }
};

struct Cons {
  uint32_t sb;
  uint32_t lane, wi, w;
  uint32_t peer;
  uint32_t stc;
  Ring r;
  __device__ __forceinline__ void release(uint32_t bar) {
    if (lane < 2) mbar_arrive_cta(bar, lane);
  }
  __device__ __forceinline__ void stage_box(const uint32_t* p) {
    uint32_t b = stc & 1;
    mbar_wait(sb + B_STE + (w * 2 + b) * 8, ((stc >> 1) & 1) ^ 1);
    uint32_t row = wi * 16 + ((lane >> 3) & 1) * 8 + (lane & 7);
    uint32_t base = sb + STG_OFF + w * 16384 + b * 8192 + row * 128;
#pragma unroll
    for (int kk = 0; kk < 4; kk++) {
      uint32_t ch = (2 * kk + (lane >> 4)) ^ (lane & 7);
      stsm_x4(base + ch * 16, p[4 * kk], p[4 * kk + 1], p[4 * kk + 2], p[4 * kk + 3]);
    }
    asm volatile("fence.proxy.async.shared::cta;" ::: "memory");
    __syncwarp();
    if (lane == 0) mbar_arrive(sb + B_STF + (w * 2 + b) * 8);
    stc++;
  }
};

__device__ __forceinline__ float gelu_tanh(float g) {
  float z = g * (1.0f + 0.044715f * g * g);
  float e = ex2(z * (-2.0f * 0.7978845608028654f * 1.4426950408889634f));
  return __fdividef(g, 1.0f + e);
}
__device__ __forceinline__ float silu_f(float d) {
  float e = ex2(d * -1.4426950408889634f);
  return __fdividef(d, 1.0f + e);
}

__device__ __forceinline__ void gemm_item(Cons& c, const Params& p, uint32_t item, uint32_t rank, unsigned ep1) {
  const int type = item & 7, j = (item >> 3) & 7, idx = (item >> 6) & 31, nk = (item >> 17) & 127;
  float acc[128];
#pragma unroll
  for (int i = 0; i < 128; i++) acc[i] = 0.f;
  c.r.to_g();
  uint32_t prev = 0;
  for (int ks = 0; ks < nk; ks++) {
    uint32_t s = c.r.gs;
    mbar_wait(c.sb + B_FULLG + s * 8, (c.r.gph >> s) & 1);
    c.r.gph ^= 1u << s;
    c.r.gs = (s + 1) & 3;
    uint32_t base = c.sb + s * 49152;
    uint64_t da = mkdesc(base + c.w * 8192, 16, 1024);
    uint64_t db = mkdesc(base + 16384, 8192, 1024);
    WG_FENCE();
#pragma unroll
    for (int kk = 0; kk < 4; kk++) wgmma_ss_n256<1>(acc, da + kk * 2, db + kk * 128, 1);
    WG_COMMIT();
    if (ks > 0) {
      WG_WAIT(1);
      c.release(c.sb + B_EMPTYG + prev * 8);
    }
    prev = s;
  }
  WG_WAIT(0);
  fence_regs(acc);
  c.release(c.sb + B_EMPTYG + prev * 8);

  const int mt = 2 * j + rank;
  uint32_t pk[16];
  if (type == IT_KV) {
#pragma unroll
    for (int b = 0; b < 4; b++) {
#pragma unroll
      for (int i = 0; i < 16; i++) pk[i] = pack_bf16(acc[b * 32 + 2 * i], acc[b * 32 + 2 * i + 1]);
      c.stage_box(pk);
    }
  } else if (type == IT_GU) {
#pragma unroll
    for (int b = 0; b < 2; b++) {
#pragma unroll
      for (int i = 0; i < 16; i++) {
        float g0 = round_bf16(acc[b * 32 + 2 * i]), g1 = round_bf16(acc[b * 32 + 2 * i + 1]);
        float u0 = round_bf16(acc[64 + b * 32 + 2 * i]), u1 = round_bf16(acc[64 + b * 32 + 2 * i + 1]);
        pk[i] = pack_bf16(round_bf16(gelu_tanh(g0)) * u0, round_bf16(gelu_tanh(g1)) * u1);
      }
      c.stage_box(pk);
    }
  } else if (type == IT_DN) {
#pragma unroll
    for (int b = 0; b < 4; b++) {
#pragma unroll
      for (int i = 0; i < 16; i++)
        pk[i] = pack_bf16(silu_f(round_bf16(acc[b * 32 + 2 * i])), silu_f(round_bf16(acc[b * 32 + 2 * i + 1])));
      c.stage_box(pk);
    }
  } else {
    const int row0 = mt * 128 + c.w * 64 + c.wi * 16 + (c.lane >> 2);
    const int col0 = idx * 256 + (c.lane & 3) * 2;
    unsigned* pf = &g_flags[F_PART + (mt * 2 + idx) * 8 + c.w * 4 + c.wi];
    if (((item >> 24) & 1) == 0) {
      float* d0 = g_part + row0 * DM + col0;
#pragma unroll
      for (int b = 0; b < 32; b++) {
        asm volatile("red.global.add.v2.f32 [%0], {%1, %2};" ::"l"(d0 + b * 8), "f"(acc[4 * b]), "f"(acc[4 * b + 1]) : "memory");
        asm volatile("red.global.add.v2.f32 [%0], {%1, %2};" ::"l"(d0 + 8 * DM + b * 8), "f"(acc[4 * b + 2]), "f"(acc[4 * b + 3]) : "memory");
      }
      __threadfence();
      __syncwarp();
      if (c.lane == 0) red_release(pf);
    } else {
      const unsigned np = (item >> 25) & 15;
      if (c.lane == 0) {
        wait_flag(pf, ep1 * np);
        wait_flag(&g_flags[F_G + (mt * 2 + idx) * 2 + c.w], ep1);
      }
      __syncwarp();
      const float* d0 = g_part + row0 * DM + col0;
      const bf16* x0 = p.x + row0 * DM + col0;
      const bf16* g0 = g_g + row0 * DM + col0;
#pragma unroll
      for (int b = 0; b < 4; b++) {
#pragma unroll
        for (int i = 0; i < 16; i++) {
          const int off = (i & 1) * 8 * DM + b * 64 + (i >> 1) * 8;
          float2 pv = make_float2(0.f, 0.f);
          if (np) pv = __ldcg((const float2*)(d0 + off));
          uint32_t xv = __ldg((const uint32_t*)(x0 + off));
          uint32_t gv = __ldcg((const uint32_t*)(g0 + off));
          float s0 = round_bf16(acc[b * 32 + 2 * i] + pv.x), s1 = round_bf16(acc[b * 32 + 2 * i + 1] + pv.y);
          float o0 = __uint_as_float(xv << 16) + round_bf16(s0 * __uint_as_float(gv << 16));
          float o1 = __uint_as_float(xv & 0xffff0000u) + round_bf16(s1 * __uint_as_float(gv & 0xffff0000u));
          pk[i] = pack_bf16(o0, o1);
        }
        c.stage_box(pk);
      }
    }
  }
}

struct Slot { uint32_t s, ph; };
__device__ __forceinline__ Slot take_a(Ring& r) {
  Slot t;
  t.s = r.as;
  t.ph = (r.aph >> t.s) & 1;
  r.aph ^= 1u << t.s;
  r.as = (t.s == 5) ? 0 : t.s + 1;
  return t;
}

__device__ __forceinline__ void qk_issue(float (&S)[64], uint32_t qbase, uint32_t kbase) {
  uint64_t da = mkdesc(qbase, 16, 1024);
  uint64_t db = mkdesc(kbase, 16, 1024);
#pragma unroll
  for (int kk = 0; kk < 8; kk++)
    wgmma_ss_n128<0>(S, da + (kk >> 2) * 512 + (kk & 3) * 2, db + (kk >> 2) * 1024 + (kk & 3) * 2, kk != 0);
}
__device__ __forceinline__ void pv_issue(float (&O)[64], const uint32_t (&P)[32], uint32_t vbase) {
  uint64_t db = mkdesc(vbase, 16384, 1024);
#pragma unroll
  for (int kk = 0; kk < 8; kk++)
    wgmma_rs_n128<1>(O, P[4 * kk], P[4 * kk + 1], P[4 * kk + 2], P[4 * kk + 3], db + kk * 128, 1);
}

__device__ __forceinline__ void attn_item(Cons& c, uint32_t item, uint32_t rank) {
  const int j = (item >> 3) & 7;
  const bool heavy = (((item >> 24) & 1) == rank);
  const int nblk = 2 * j + (heavy ? 2 : 1);
  constexpr float CS = 0.08838834764831845f * 1.4426950408889634f;
  float S[64], O[64];
  uint32_t P[32];
  const uint32_t qbase = c.sb + STG_OFF + c.w * 16384;
  c.r.to_a();
  {
    uint32_t px = 0, pw = 0;
#pragma unroll
    for (int i = 0; i < 64; i++) S[i] = 0.f;
#pragma unroll 1
    for (int ch = 0; ch < 4; ch++) {
      Slot tx = take_a(c.r), tw = take_a(c.r);
      mbar_wait(c.sb + B_FULLA + tx.s * 8, tx.ph);
      mbar_wait(c.sb + B_FULLA + tw.s * 8, tw.ph);
      uint64_t da = mkdesc(c.sb + tx.s * 32768 + c.w * 8192, 16, 1024);
      uint64_t db = mkdesc(c.sb + tw.s * 32768, 16384, 1024);
      WG_FENCE();
#pragma unroll
      for (int kk = 0; kk < 8; kk++) wgmma_ss_n128<1>(S, da + (kk >> 2) * 1024 + (kk & 3) * 2, db + kk * 128, 1);
      WG_COMMIT();
      if (ch > 0) {
        WG_WAIT(1);
        c.release(c.sb + B_EMPTYA + px * 8);
        c.release(c.sb + B_EMPTYA + pw * 8);
      }
      px = tx.s; pw = tw.s;
    }
    WG_WAIT(0);
    fence_regs(S);
    c.release(c.sb + B_EMPTYA + px * 8);
    c.release(c.sb + B_EMPTYA + pw * 8);
    mbar_wait(c.sb + B_STE + (c.w * 2 + (c.stc & 1)) * 8, ((c.stc >> 1) & 1) ^ 1);
    mbar_wait(c.sb + B_STE + (c.w * 2 + ((c.stc + 1) & 1)) * 8, (((c.stc + 1) >> 1) & 1) ^ 1);
    const uint32_t row = c.wi * 16 + ((c.lane >> 3) & 1) * 8 + (c.lane & 7);
#pragma unroll
    for (int kk = 0; kk < 8; kk++) {
      const uint32_t ch = (2 * (kk & 3) + (c.lane >> 4)) ^ (c.lane & 7);
      stsm_x4(qbase + (kk >> 2) * 8192 + row * 128 + ch * 16, pack_bf16(S[8 * kk], S[8 * kk + 1]), pack_bf16(S[8 * kk + 2], S[8 * kk + 3]),
              pack_bf16(S[8 * kk + 4], S[8 * kk + 5]), pack_bf16(S[8 * kk + 6], S[8 * kk + 7]));
    }
    asm volatile("fence.proxy.async.shared::cta;" ::: "memory");
  }
  if (!heavy) {
    Slot t = take_a(c.r);
    mbar_wait(c.sb + B_FULLA + t.s * 8, t.ph);
    c.release(c.sb + B_EMPTYA + t.s * 8);
  }
  float m0, m1, l0, l1;
  {
    Slot tk = take_a(c.r);
    mbar_wait(c.sb + B_FULLA + tk.s * 8, tk.ph);
    bar_sync(1 + c.w, 256);
    WG_FENCE();
    qk_issue(S, qbase, c.sb + tk.s * 32768);
    WG_COMMIT();
    bar_arrive(2 - c.w, 256);
    WG_WAIT(0);
    fence_regs(S);
    c.release(c.sb + B_EMPTYA + tk.s * 8);
    const int r0 = c.w * 64 + c.wi * 16 + (c.lane >> 2);
    const int cb = (c.lane & 3) * 2;
    m0 = -INFINITY; m1 = -INFINITY;
#pragma unroll
    for (int b = 0; b < 16; b++) {
      int col = b * 8 + cb;
      if (col > r0) S[4 * b] = -INFINITY;
      if (col + 1 > r0) S[4 * b + 1] = -INFINITY;
      if (col > r0 + 8) S[4 * b + 2] = -INFINITY;
      if (col + 1 > r0 + 8) S[4 * b + 3] = -INFINITY;
      m0 = fmaxf(m0, fmaxf(S[4 * b], S[4 * b + 1]));
      m1 = fmaxf(m1, fmaxf(S[4 * b + 2], S[4 * b + 3]));
    }
    m0 = fmaxf(m0, __shfl_xor_sync(0xffffffffu, m0, 1));
    m1 = fmaxf(m1, __shfl_xor_sync(0xffffffffu, m1, 1));
    m0 = fmaxf(m0, __shfl_xor_sync(0xffffffffu, m0, 2));
    m1 = fmaxf(m1, __shfl_xor_sync(0xffffffffu, m1, 2));
    const float n0 = -m0 * CS, n1 = -m1 * CS;
    l0 = 0.f; l1 = 0.f;
#pragma unroll
    for (int b = 0; b < 16; b++) {
      float a0 = ex2(fmaf(S[4 * b], CS, n0)), a1 = ex2(fmaf(S[4 * b + 1], CS, n0));
      float a2 = ex2(fmaf(S[4 * b + 2], CS, n1)), a3 = ex2(fmaf(S[4 * b + 3], CS, n1));
      l0 += a0 + a1; l1 += a2 + a3;
      P[2 * b] = pack_bf16(a0, a1);
      P[2 * b + 1] = pack_bf16(a2, a3);
    }
  }
  if (!heavy) {
    Slot t = take_a(c.r);
    mbar_wait(c.sb + B_FULLA + t.s * 8, t.ph);
    c.release(c.sb + B_EMPTYA + t.s * 8);
  }
#pragma unroll
  for (int i = 0; i < 64; i++) O[i] = 0.f;
#pragma unroll 1
  for (int it = 1; it < nblk; it++) {
    Slot tk = take_a(c.r), tv = take_a(c.r);
    mbar_wait(c.sb + B_FULLA + tk.s * 8, tk.ph);
    mbar_wait(c.sb + B_FULLA + tv.s * 8, tv.ph);
    bar_sync(1 + c.w, 256);
    fence_regs(P);
    fence_regs(O);
    WG_FENCE();
    qk_issue(S, qbase, c.sb + tk.s * 32768);
    WG_COMMIT();
    pv_issue(O, P, c.sb + tv.s * 32768);
    WG_COMMIT();
    bar_arrive(2 - c.w, 256);
    WG_WAIT(1);
    fence_regs(S);
    c.release(c.sb + B_EMPTYA + tk.s * 8);
    float x0 = m0, x1 = m1;
#pragma unroll
    for (int b = 0; b < 16; b++) {
      x0 = fmaxf(x0, fmaxf(S[4 * b], S[4 * b + 1]));
      x1 = fmaxf(x1, fmaxf(S[4 * b + 2], S[4 * b + 3]));
    }
    x0 = fmaxf(x0, __shfl_xor_sync(0xffffffffu, x0, 1));
    x1 = fmaxf(x1, __shfl_xor_sync(0xffffffffu, x1, 1));
    x0 = fmaxf(x0, __shfl_xor_sync(0xffffffffu, x0, 2));
    x1 = fmaxf(x1, __shfl_xor_sync(0xffffffffu, x1, 2));
    const float n0 = -x0 * CS, n1 = -x1 * CS;
    const float sc0 = ex2(fmaf(m0, CS, n0)), sc1 = ex2(fmaf(m1, CS, n1));
    m0 = x0; m1 = x1;
    l0 *= sc0; l1 *= sc1;
#pragma unroll
    for (int b = 0; b < 16; b++) {
      S[4 * b] = ex2(fmaf(S[4 * b], CS, n0));
      S[4 * b + 1] = ex2(fmaf(S[4 * b + 1], CS, n0));
      S[4 * b + 2] = ex2(fmaf(S[4 * b + 2], CS, n1));
      S[4 * b + 3] = ex2(fmaf(S[4 * b + 3], CS, n1));
      l0 += S[4 * b] + S[4 * b + 1];
      l1 += S[4 * b + 2] + S[4 * b + 3];
    }
    WG_WAIT(0);
    fence_regs(O);
    fence_regs(P);
    c.release(c.sb + B_EMPTYA + tv.s * 8);
#pragma unroll
    for (int b = 0; b < 16; b++) {
      O[4 * b] *= sc0; O[4 * b + 1] *= sc0; O[4 * b + 2] *= sc1; O[4 * b + 3] *= sc1;
      P[2 * b] = pack_bf16(S[4 * b], S[4 * b + 1]);
      P[2 * b + 1] = pack_bf16(S[4 * b + 2], S[4 * b + 3]);
    }
  }
  {
    Slot tv = take_a(c.r);
    mbar_wait(c.sb + B_FULLA + tv.s * 8, tv.ph);
    fence_regs(P);
    fence_regs(O);
    WG_FENCE();
    pv_issue(O, P, c.sb + tv.s * 32768);
    WG_COMMIT();
    l0 += __shfl_xor_sync(0xffffffffu, l0, 1);
    l1 += __shfl_xor_sync(0xffffffffu, l1, 1);
    l0 += __shfl_xor_sync(0xffffffffu, l0, 2);
    l1 += __shfl_xor_sync(0xffffffffu, l1, 2);
    const float i0 = 1.0f / l0, i1 = 1.0f / l1;
    WG_WAIT(0);
    fence_regs(O);
    c.release(c.sb + B_EMPTYA + tv.s * 8);
    uint32_t pk[16];
#pragma unroll
    for (int b = 0; b < 2; b++) {
#pragma unroll
      for (int i = 0; i < 8; i++) {
        pk[2 * i] = pack_bf16(O[b * 32 + 4 * i] * i0, O[b * 32 + 4 * i + 1] * i0);
        pk[2 * i + 1] = pack_bf16(O[b * 32 + 4 * i + 2] * i1, O[b * 32 + 4 * i + 3] * i1);
      }
      c.stage_box(pk);
    }
  }
}

struct Prod {
  uint32_t sb;
  Ring r;
  __device__ __forceinline__ uint32_t acquire_g() {
    uint32_t s = r.gs;
    mbar_wait(sb + B_EMPTYG + s * 8, (r.gph >> s) & 1);
    uint32_t a0 = s + (s >> 1);
    mbar_wait(sb + B_EMPTYA + a0 * 8, (r.aph >> a0) & 1);
    mbar_wait(sb + B_EMPTYA + (a0 + 1) * 8, (r.aph >> (a0 + 1)) & 1);
    r.gph ^= 1u << s;
    r.gs = (s + 1) & 3;
    mbar_expect_tx(sb + B_FULLG + s * 8, 49152);
    return s;
  }
  __device__ __forceinline__ uint32_t acquire_a() {
    uint32_t s = r.as;
    mbar_wait(sb + B_EMPTYA + s * 8, (r.aph >> s) & 1);
    uint32_t g0 = (s * 2) / 3, g1 = (s * 2 + 1) / 3;
    mbar_wait(sb + B_EMPTYG + g0 * 8, (r.gph >> g0) & 1);
    mbar_wait(sb + B_EMPTYG + g1 * 8, (r.gph >> g1) & 1);
    r.aph ^= 1u << s;
    r.as = (s == 5) ? 0 : s + 1;
    mbar_expect_tx(sb + B_FULLA + s * 8, 32768);
    return s;
  }
};

__global__ void __cluster_dims__(2, 1, 1) __launch_bounds__(NTHREADS, 1)
mega_kernel(const __grid_constant__ Params p) {
  extern __shared__ uint8_t smem_raw[];
  const uint32_t sb = (smem_u32(smem_raw) + 1023) & ~1023u;
  const uint32_t tid = threadIdx.x, lane = tid & 31;
  const uint32_t warp = __shfl_sync(0xffffffffu, tid >> 5, 0);
  uint32_t rank;
  asm volatile("mov.u32 %0, %%cluster_ctarank;" : "=r"(rank));
  const uint32_t cl = blockIdx.x >> 1;
  const int i_beg = p.off[cl], i_end = p.off[cl + 1];

  unsigned ep1;
  asm volatile("ld.relaxed.gpu.global.u32 %0, [%1];" : "=r"(ep1) : "l"(&g_epoch) : "memory");
  ep1 += 1;

  if (tid == 0) {
    for (int i = 0; i < 4; i++) { mbar_init(sb + B_FULLG + i * 8, 1); mbar_init(sb + B_EMPTYG + i * 8, 16); }
    for (int i = 0; i < 6; i++) { mbar_init(sb + B_FULLA + i * 8, 1); mbar_init(sb + B_EMPTYA + i * 8, 16); }
    for (int i = 0; i < 4; i++) { mbar_init(sb + B_STF + i * 8, 4); mbar_init(sb + B_STE + i * 8, 1); }
    mbar_init(sb + B_DONE, 11);
    asm volatile("fence.mbarrier_init.release.cluster;" ::: "memory");
  }
  __syncthreads();
  cluster_sync();

  if (warp < 4) {
    asm volatile("setmaxnreg.dec.sync.aligned.u32 40;");
    if (warp == 0) {
      Prod pr;
      pr.sb = sb;
      pr.r.gs = 0; pr.r.as = 0; pr.r.gph = 0xf; pr.r.aph = 0x3f; pr.r.mode = 0;
      for (int n = i_beg; n < i_end; n++) {
        const uint32_t item = p.items[n];
        const int type = item & 7, j = (item >> 3) & 7, idx = (item >> 6) & 31;
        const int k0 = (item >> 11) & 63, nk = (item >> 17) & 127;
        {
          const unsigned* fp = nullptr;
          unsigned cnt = 0;
          const int mt = 2 * j + rank;
          if (type == IT_GU) {
            if (lane == 0) { fp = &g_flags[F_LN + mt]; cnt = 64; }
          } else if (type == IT_DN) {
            if (lane == 0) { fp = &g_flags[F_H + mt]; cnt = 28; }
          } else if (type == IT_OP) {
            const int h0 = k0 >> 1, h1 = (k0 + nk - 1) >> 1;
            if ((int)lane >= h0 && (int)lane <= h1) { fp = &g_flags[F_CTX + mt * 32 + lane]; cnt = 2; }
          } else if (type == IT_AT) {
            const int qt = 2 * j + ((((item >> 24) & 1) == rank) ? 1 : 0);
            if ((int)lane < 2 * j + 2) { fp = &g_flags[F_KV + idx * 16 + lane]; cnt = 2; }
            else if (lane == 31) { fp = &g_flags[F_LN + qt]; cnt = 64; }
          }
          if (fp) wait_flag(fp, ep1 * cnt);
          __syncwarp();
          asm volatile("fence.proxy.async;" ::: "memory");
        }
        if (lane == 0) {
          if (type != IT_AT) {
            pr.r.to_g();
            const CUtensorMap* ta = &p.tm[type == IT_KV ? TM_CKV : type == IT_GU ? TM_XN : type == IT_DN ? TM_H : TM_CTX];
            const CUtensorMap* tb = &p.tm[type == IT_KV ? TM_WUK + rank : type == IT_GU ? TM_WG + rank : type == IT_DN ? TM_WD : TM_WO];
            const int grp = (type <= IT_GU) ? idx * 2 : idx * 4 + rank * 2;
            const int arow = (2 * j + rank) * 128;
            for (int ks = k0; ks < k0 + nk; ks++) {
              uint32_t s = pr.acquire_g();
              uint32_t fb = sb + B_FULLG + s * 8;
              tma_load_2d(sb + s * 49152, ta, fb, ks * 64, arow);
              tma_load_3d_mc(sb + s * 49152 + 16384 + rank * 16384, tb, fb, 0, ks * 64, grp);
            }
          } else {
            pr.r.to_a();
            const int qt = 2 * j + ((((item >> 24) & 1) == rank) ? 1 : 0);
            for (int ch = 0; ch < 4; ch++) {
              uint32_t s = pr.acquire_a();
              uint32_t fb = sb + B_FULLA + s * 8;
              tma_load_2d(sb + s * 32768, &p.tm[TM_XN], fb, ch * 128, qt * 128);
              tma_load_2d(sb + s * 32768 + 16384, &p.tm[TM_XN], fb, ch * 128 + 64, qt * 128);
              s = pr.acquire_a();
              fb = sb + B_FULLA + s * 8;
              tma_load_2d_mc(sb + s * 32768 + rank * 16384, &p.tm[TM_WQ], fb, idx * 128 + rank * 64, ch * 128);
            }
            const int nb = 2 * j + 2;
            const int kc = idx * 256 + rank * 64;
            for (int i = 0; i <= nb; i++) {
              if (i < nb) {
                uint32_t s = pr.acquire_a();
                tma_load_2d_mc(sb + s * 32768 + rank * 16384, &p.tm[TM_KVL], sb + B_FULLA + s * 8, kc, (nb - 1 - i) * 128);
              }
              if (i > 0) {
                uint32_t s = pr.acquire_a();
                tma_load_2d_mc(sb + s * 32768 + rank * 16384, &p.tm[TM_KVL], sb + B_FULLA + s * 8, kc + 128, (nb - i) * 128);
              }
            }
          }
        }
        __syncwarp();
      }
      if (lane == 0) mbar_arrive(sb + B_DONE);
    } else if (warp < 3) {
      if (lane == 0) {
        const uint32_t w = warp - 1;
        uint32_t stc = 0;
        for (int n = i_beg; n < i_end; n++) {
          const uint32_t item = p.items[n];
          const int type = item & 7, j = (item >> 3) & 7, idx = (item >> 6) & 31;
          int mt = 2 * j + rank, nbox = 4, col = idx * 256, tmi;
          unsigned* fp = nullptr;
          if (type == IT_KV) { tmi = TM_KVS; fp = &g_flags[F_KV + idx * 16 + mt]; }
          else if (type == IT_GU) { tmi = TM_HS; nbox = 2; col = idx * 128; fp = &g_flags[F_H + mt]; }
          else if (type == IT_DN) { tmi = TM_GS; fp = &g_flags[F_G + (mt * 2 + idx) * 2 + w]; }
          else if (type == IT_OP) { tmi = TM_OUTS; if (((item >> 24) & 1) == 0) nbox = 0; }
          else {
            mt = 2 * j + ((((item >> 24) & 1) == rank) ? 1 : 0);
            tmi = TM_CTXS; nbox = 2; col = idx * 128; fp = &g_flags[F_CTX + mt * 32 + idx];
          }
          for (int b = 0; b < nbox; b++) {
            const uint32_t bb = stc & 1;
            mbar_wait(sb + B_STF + (w * 2 + bb) * 8, (stc >> 1) & 1);
            tma_store_2d(&p.tm[tmi], sb + STG_OFF + w * 16384 + bb * 8192, col + b * 64, mt * 128 + w * 64);
            asm volatile("cp.async.bulk.commit_group;" ::: "memory");
            asm volatile("cp.async.bulk.wait_group.read 0;" ::: "memory");
            mbar_arrive(sb + B_STE + (w * 2 + bb) * 8);
            stc++;
          }
          if (nbox) {
            asm volatile("cp.async.bulk.wait_group 0;" ::: "memory");
            if (fp) { __threadfence(); red_release(fp); }
          }
        }
        mbar_arrive(sb + B_DONE);
      }
      __syncwarp();
    } else {
      if (lane == 0) {
        red_release(&g_flags[F_START]);
        if (blockIdx.x == 0) {
          wait_flag(&g_flags[F_START], ep1 * gridDim.x);
          asm volatile("st.relaxed.gpu.global.u32 [%0], %1;" ::"l"(&g_epoch), "r"(ep1) : "memory");
        }
        mbar_wait(sb + B_DONE, 0);
      }
      __syncwarp();
    }
    cluster_sync();
  } else {
    asm volatile("setmaxnreg.inc.sync.aligned.u32 232;");
    Cons c;
    c.sb = sb; c.lane = lane; c.wi = warp & 3; c.w = (warp >> 2) - 1; c.stc = 0;
    c.r.gs = 0; c.r.as = 0; c.r.gph = 0; c.r.aph = 0; c.r.mode = 0;
    for (int rb = blockIdx.x; rb < 128; rb += gridDim.x) {
#pragma unroll
      for (int rr = 0; rr < 2; rr++) {
        const int row = rb * 16 + (warp - 4) * 2 + rr;
        const uint4* src = (const uint4*)(p.x + row * DM);
        uint4 v0 = __ldg(src + lane), v1 = __ldg(src + 32 + lane);
        uint32_t u[8] = {v0.x, v0.y, v0.z, v0.w, v1.x, v1.y, v1.z, v1.w};
        float f[16];
        float sum = 0.f;
#pragma unroll
        for (int i = 0; i < 8; i++) {
          f[2 * i] = __uint_as_float(u[i] << 16);
          f[2 * i + 1] = __uint_as_float(u[i] & 0xffff0000u);
          sum += f[2 * i] + f[2 * i + 1];
        }
#pragma unroll
        for (int o = 16; o; o >>= 1) sum += __shfl_xor_sync(0xffffffffu, sum, o);
        const float mean = sum * (1.0f / DM);
        float vs = 0.f;
#pragma unroll
        for (int i = 0; i < 16; i++) { float d = f[i] - mean; vs += d * d; }
#pragma unroll
        for (int o = 16; o; o >>= 1) vs += __shfl_xor_sync(0xffffffffu, vs, o);
        const float mb = round_bf16(mean);
        const float den = round_bf16(sqrtf(round_bf16(round_bf16(vs * (1.0f / DM)) + 1e-5f)));
#pragma unroll
        for (int i = 0; i < 8; i++)
          u[i] = pack_bf16(round_bf16(f[2 * i] - mb) / den, round_bf16(f[2 * i + 1] - mb) / den);
        uint4* dst = (uint4*)(g_xn + row * DM);
        dst[lane] = make_uint4(u[0], u[1], u[2], u[3]);
        dst[32 + lane] = make_uint4(u[4], u[5], u[6], u[7]);
        float4* z = (float4*)(g_part + row * DM);
#pragma unroll
        for (int i = 0; i < 4; i++) z[i * 32 + lane] = make_float4(0.f, 0.f, 0.f, 0.f);
      }
      asm volatile("fence.proxy.async;" ::: "memory");
      __threadfence();
      __syncwarp();
      if (lane == 0) red_release(&g_flags[F_LN + (rb >> 3)]);
    }
    if (c.w == 1) bar_arrive(1, 256);
    for (int n = i_beg; n < i_end; n++) {
      const uint32_t item = p.items[n];
      if ((item & 7) == IT_AT) attn_item(c, item, rank);
      else gemm_item(c, p, item, rank, ep1);
    }
    if (lane == 0) mbar_arrive(sb + B_DONE);
    cluster_sync();
  }
}

typedef CUresult (*EncFn)(CUtensorMap*, CUtensorMapDataType, cuuint32_t, void*, const cuuint64_t*, const cuuint64_t*,
                          const cuuint32_t*, const cuuint32_t*, CUtensorMapInterleave, CUtensorMapSwizzle,
                          CUtensorMapL2promotion, CUtensorMapFloatOOBfill);

static void enc2d(EncFn enc, CUtensorMap* m, const void* ptr, uint64_t cols, uint64_t rows, uint32_t bc, uint32_t br) {
  cuuint64_t gd[2] = {cols, rows};
  cuuint64_t gs[1] = {cols * 2};
  cuuint32_t bd[2] = {bc, br}, es[2] = {1, 1};
  enc(m, CU_TENSOR_MAP_DATA_TYPE_BFLOAT16, 2, (void*)ptr, gd, gs, bd, es, CU_TENSOR_MAP_INTERLEAVE_NONE,
      CU_TENSOR_MAP_SWIZZLE_128B, CU_TENSOR_MAP_L2_PROMOTION_L2_256B, CU_TENSOR_MAP_FLOAT_OOB_FILL_NONE);
}
static void enc3d(EncFn enc, CUtensorMap* m, const void* ptr, uint64_t cols, uint64_t rows) {
  cuuint64_t gd[3] = {64, rows, cols / 64};
  cuuint64_t gs[2] = {cols * 2, 128};
  cuuint32_t bd[3] = {64, 64, 2}, es[3] = {1, 1, 1};
  enc(m, CU_TENSOR_MAP_DATA_TYPE_BFLOAT16, 3, (void*)ptr, gd, gs, bd, es, CU_TENSOR_MAP_INTERLEAVE_NONE,
      CU_TENSOR_MAP_SWIZZLE_128B, CU_TENSOR_MAP_L2_PROMOTION_L2_256B, CU_TENSOR_MAP_FLOAT_OOB_FILL_NONE);
}

struct SItem { int type, j, idx, k0, nk, fin, np; double cost; double done; int assigned; };

static void build_schedule(Params& P, int ncl) {
  static SItem it[MAX_ITEMS];
  int n = 0;
  const int OPS = 4;
  auto add = [&](int type, int j, int idx, int k0, int nk, int fin, int np, double cost) {
    it[n].type = type; it[n].j = j; it[n].idx = idx; it[n].k0 = k0; it[n].nk = nk; it[n].fin = fin; it[n].np = np;
    it[n].cost = cost; it[n].done = -1; it[n].assigned = 0; n++;
  };
  int kv0 = n;
  for (int h = 0; h < 32; h++) for (int j = 0; j < 8; j++) add(IT_KV, j, h, 0, 8, 0, 0, 8900);
  int gu0 = n;
  for (int j = 0; j < 8; j++) for (int f = 0; f < 14; f++) add(IT_GU, j, f, 0, 8, 0, 0, 8900);
  int dn0 = n;
  for (int j = 0; j < 8; j++) for (int c = 0; c < 2; c++) add(IT_DN, j, c, 0, 28, 0, 0, 28 * 1050 + 800);
  int at0 = n;
  for (int j = 7; j >= 0; j--) for (int h = 0; h < 32; h++) add(IT_AT, j, h, 0, 0, 0, 0, 4400 + (2 * j + 1.5) * 2600 + 500);
  int op0 = n;
  for (int j = 7; j >= 0; j--) for (int s = 0; s < OPS; s++) for (int c = 0; c < 2; c++)
    add(IT_OP, j, c, s * (64 / OPS), 64 / OPS, s == OPS - 1, OPS - 1, (64 / OPS) * 1050 + 2000);
  auto ready = [&](int i) -> double {
    double t = 0;
    auto dep = [&](int d) { if (t >= 0) { if (!it[d].assigned) t = -1; else if (it[d].done > t) t = it[d].done; } };
    const SItem& a = it[i];
    if (a.type == IT_GU) t = 4000;
    else if (a.type == IT_DN) { for (int f = 0; f < 14; f++) dep(gu0 + a.j * 14 + f); }
    else if (a.type == IT_AT) { for (int j = 0; j <= a.j; j++) dep(kv0 + a.idx * 8 + j); }
    else if (a.type == IT_OP) {
      for (int h = a.k0 / 2; h <= (a.k0 + a.nk - 1) / 2; h++) dep(at0 + (7 - a.j) * 32 + h);
      if (a.fin) {
        dep(dn0 + a.j * 2 + a.idx);
        for (int s = 0; s < OPS - 1; s++) {
          int d = op0 + ((7 - a.j) * OPS + s) * 2 + a.idx;
          if (t >= 0) { if (!it[d].assigned) t = -1; else if (it[d].done - a.cost > t) t = it[d].done - a.cost; }
        }
      }
    }
    return t;
  };
  static int list[MAX_CL][64];
  int cnt[MAX_CL];
  double tfree[MAX_CL];
  int par[MAX_CL];
  for (int c = 0; c < ncl; c++) { cnt[c] = 0; tfree[c] = 0; par[c] = 0; }
  for (int left = n; left > 0; left--) {
    int c = 0;
    for (int k = 1; k < ncl; k++) if (tfree[k] < tfree[c]) c = k;
    int best = -1; double bt = 1e30;
    for (int i = 0; i < n; i++) {
      if (it[i].assigned) continue;
      double r = ready(i);
      if (r < 0) continue;
      r += 1500;
      if (r <= tfree[c] || it[i].type == IT_KV) { best = i; bt = tfree[c]; break; }
      if (r < bt) { bt = r; best = i; }
    }
    it[best].assigned = 1;
    it[best].done = bt + it[best].cost;
    tfree[c] = it[best].done;
    list[c][cnt[c]++] = best;
  }
  int o = 0;
  for (int c = 0; c < ncl; c++) {
    P.off[c] = (uint16_t)o;
    for (int k = 0; k < cnt[c]; k++) {
      const SItem& a = it[list[c][k]];
      int flag = a.fin;
      if (a.type == IT_AT) { flag = par[c]; par[c] ^= 1; }
      P.items[o++] = mk_item(a.type, a.j, a.idx, a.k0, a.nk, flag, a.np);
    }
  }
  P.off[ncl] = (uint16_t)o;
}

}

extern "C" void kernel_launch(void* const* d_in, const int* in_sizes, int n_in, void* d_out, int out_size) {
  using namespace mk;
  static Params P;
  static int ncl = 0;
  static const void* cached[11];
  bool same = ncl > 0 && cached[10] == d_out;
  for (int i = 0; i < 10 && same; i++) same = cached[i] == d_in[i];
  if (!same) {
    void* fn = nullptr;
    cudaDriverEntryPointQueryResult qr;
    cudaGetDriverEntryPoint("cuTensorMapEncodeTiled", &fn, cudaEnableDefault, &qr);
    EncFn enc = (EncFn)fn;
    void *xn, *kv, *h, *ctx, *g;
    cudaGetSymbolAddress(&xn, g_xn);
    cudaGetSymbolAddress(&kv, g_kv);
    cudaGetSymbolAddress(&h, g_h);
    cudaGetSymbolAddress(&ctx, g_ctx);
    cudaGetSymbolAddress(&g, g_g);
    enc2d(enc, &P.tm[TM_XN], xn, 512, SEQ, 64, 128);
    enc2d(enc, &P.tm[TM_CKV], d_in[1], 512, SEQ, 64, 128);
    enc2d(enc, &P.tm[TM_H], h, DFF, SEQ, 64, 128);
    enc2d(enc, &P.tm[TM_CTX], ctx, 4096, SEQ, 64, 128);
    enc3d(enc, &P.tm[TM_WUK], d_in[3], 4096, 512);
    enc3d(enc, &P.tm[TM_WUV], d_in[4], 4096, 512);
    enc3d(enc, &P.tm[TM_WG], d_in[7], DFF, 512);
    enc3d(enc, &P.tm[TM_WU], d_in[8], DFF, 512);
    enc3d(enc, &P.tm[TM_WD], d_in[9], 512, DFF);
    enc3d(enc, &P.tm[TM_WO], d_in[5], 512, 4096);
    enc2d(enc, &P.tm[TM_WQ], d_in[2], 4096, 512, 64, 128);
    enc2d(enc, &P.tm[TM_KVL], kv, 8192, SEQ, 64, 128);
    enc2d(enc, &P.tm[TM_KVS], kv, 8192, SEQ, 64, 64);
    enc2d(enc, &P.tm[TM_HS], h, DFF, SEQ, 64, 64);
    enc2d(enc, &P.tm[TM_CTXS], ctx, 4096, SEQ, 64, 64);
    enc2d(enc, &P.tm[TM_GS], g, 512, SEQ, 64, 64);
    enc2d(enc, &P.tm[TM_OUTS], d_out, 512, SEQ, 64, 64);
    P.x = (const bf16*)d_in[0];
    P.out = (bf16*)d_out;
    cudaFuncSetAttribute(mega_kernel, cudaFuncAttributeMaxDynamicSharedMemorySize, SMEM_BYTES);
    if (ncl == 0) {
      cudaLaunchConfig_t cfg = {};
      cfg.gridDim = dim3(132); cfg.blockDim = dim3(NTHREADS); cfg.dynamicSmemBytes = SMEM_BYTES;
      cudaLaunchAttribute at[1];
      at[0].id = cudaLaunchAttributeClusterDimension;
      at[0].val.clusterDim.x = 2; at[0].val.clusterDim.y = 1; at[0].val.clusterDim.z = 1;
      cfg.attrs = at; cfg.numAttrs = 1;
      int nc = 0;
      if (cudaOccupancyMaxActiveClusters(&nc, mega_kernel, &cfg) != cudaSuccess || nc < 1) { nc = 66; (void)cudaGetLastError(); }
      if (nc > MAX_CL) nc = MAX_CL;
      if (nc < 16) nc = 16;
      ncl = nc;
      build_schedule(P, ncl);
    }
    for (int i = 0; i < 10; i++) cached[i] = d_in[i];
    cached[10] = d_out;
  }
  mega_kernel<<<ncl * 2, NTHREADS, SMEM_BYTES>>>(P);
}
```

```cpp
#include <cuda_runtime.h>
#include <cuda_bf16.h>
#include <cuda.h>
#include <stdint.h>
#include <string.h>

typedef __nv_bfloat16 bf16;

template<int TB>
__device__ __forceinline__ void wgmma_ss_n256(float (&d)[128], uint64_t da, uint64_t db, int scale_d) {
  asm volatile("{\n.reg .pred p;\nsetp.ne.b32 p, %130, 0;\n"
    "wgmma.mma_async.sync.aligned.m64n256k16.f32.bf16.bf16 {%0, %1, %2, %3, %4, %5, %6, %7, %8, %9, %10, %11, %12, %13, %14, %15, %16, %17, %18, %19, %20, %21, %22, %23, %24, %25, %26, %27, %28, %29, %30, %31, %32, %33, %34, %35, %36, %37, %38, %39, %40, %41, %42, %43, %44, %45, %46, %47, %48, %49, %50, %51, %52, %53, %54, %55, %56, %57, %58, %59, %60, %61, %62, %63, %64, %65, %66, %67, %68, %69, %70, %71, %72, %73, %74, %75, %76, %77, %78, %79, %80, %81, %82, %83, %84, %85, %86, %87, %88, %89, %90, %91, %92, %93, %94, %95, %96, %97, %98, %99, %100, %101, %102, %103, %104, %105, %106, %107, %108, %109, %110, %111, %112, %113, %114, %115, %116, %117, %118, %119, %120, %121, %122, %123, %124, %125, %126, %127}, %128, %129, p, 1, 1, 0, %131;\n}\n"
    : "+f"(d[0]), "+f"(d[1]), "+f"(d[2]), "+f"(d[3]), "+f"(d[4]), "+f"(d[5]), "+f"(d[6]), "+f"(d[7]), "+f"(d[8]), "+f"(d[9]), "+f"(d[10]), "+f"(d[11]), "+f"(d[12]), "+f"(d[13]), "+f"(d[14]), "+f"(d[15]), "+f"(d[16]), "+f"(d[17]), "+f"(d[18]), "+f"(d[19]), "+f"(d[20]), "+f"(d[21]), "+f"(d[22]), "+f"(d[23]), "+f"(d[24]), "+f"(d[25]), "+f"(d[26]), "+f"(d[27]), "+f"(d[28]), "+f"(d[29]), "+f"(d[30]), "+f"(d[31]), "+f"(d[32]), "+f"(d[33]), "+f"(d[34]), "+f"(d[35]), "+f"(d[36]), "+f"(d[37]), "+f"(d[38]), "+f"(d[39]), "+f"(d[40]), "+f"(d[41]), "+f"(d[42]), "+f"(d[43]), "+f"(d[44]), "+f"(d[45]), "+f"(d[46]), "+f"(d[47]), "+f"(d[48]), "+f"(d[49]), "+f"(d[50]), "+f"(d[51]), "+f"(d[52]), "+f"(d[53]), "+f"(d[54]), "+f"(d[55]), "+f"(d[56]), "+f"(d[57]), "+f"(d[58]), "+f"(d[59]), "+f"(d[60]), "+f"(d[61]), "+f"(d[62]), "+f"(d[63]), "+f"(d[64]), "+f"(d[65]), "+f"(d[66]), "+f"(d[67]), "+f"(d[68]), "+f"(d[69]), "+f"(d[70]), "+f"(d[71]), "+f"(d[72]), "+f"(d[73]), "+f"(d[74]), "+f"(d[75]), "+f"(d[76]), "+f"(d[77]), "+f"(d[78]), "+f"(d[79]), "+f"(d[80]), "+f"(d[81]), "+f"(d[82]), "+f"(d[83]), "+f"(d[84]), "+f"(d[85]), "+f"(d[86]), "+f"(d[87]), "+f"(d[88]), "+f"(d[89]), "+f"(d[90]), "+f"(d[91]), "+f"(d[92]), "+f"(d[93]), "+f"(d[94]), "+f"(d[95]), "+f"(d[96]), "+f"(d[97]), "+f"(d[98]), "+f"(d[99]), "+f"(d[100]), "+f"(d[101]), "+f"(d[102]), "+f"(d[103]), "+f"(d[104]), "+f"(d[105]), "+f"(d[106]), "+f"(d[107]), "+f"(d[108]), "+f"(d[109]), "+f"(d[110]), "+f"(d[111]), "+f"(d[112]), "+f"(d[113]), "+f"(d[114]), "+f"(d[115]), "+f"(d[116]), "+f"(d[117]), "+f"(d[118]), "+f"(d[119]), "+f"(d[120]), "+f"(d[121]), "+f"(d[122]), "+f"(d[123]), "+f"(d[124]), "+f"(d[125]), "+f"(d[126]), "+f"(d[127])
    : "l"(da), "l"(db), "r"(scale_d), "n"(TB));
}

template<int TB>
__device__ __forceinline__ void wgmma_ss_n128(float (&d)[64], uint64_t da, uint64_t db, int scale_d) {
  asm volatile("{\n.reg .pred p;\nsetp.ne.b32 p, %66, 0;\n"
    "wgmma.mma_async.sync.aligned.m64n128k16.f32.bf16.bf16 {%0, %1, %2, %3, %4, %5, %6, %7, %8, %9, %10, %11, %12, %13, %14, %15, %16, %17, %18, %19, %20, %21, %22, %23, %24, %25, %26, %27, %28, %29, %30, %31, %32, %33, %34, %35, %36, %37, %38, %39, %40, %41, %42, %43, %44, %45, %46, %47, %48, %49, %50, %51, %52, %53, %54, %55, %56, %57, %58, %59, %60, %61, %62, %63}, %64, %65, p, 1, 1, 0, %67;\n}\n"
    : "+f"(d[0]), "+f"(d[1]), "+f"(d[2]), "+f"(d[3]), "+f"(d[4]), "+f"(d[5]), "+f"(d[6]), "+f"(d[7]), "+f"(d[8]), "+f"(d[9]), "+f"(d[10]), "+f"(d[11]), "+f"(d[12]), "+f"(d[13]), "+f"(d[14]), "+f"(d[15]), "+f"(d[16]), "+f"(d[17]), "+f"(d[18]), "+f"(d[19]), "+f"(d[20]), "+f"(d[21]), "+f"(d[22]), "+f"(d[23]), "+f"(d[24]), "+f"(d[25]), "+f"(d[26]), "+f"(d[27]), "+f"(d[28]), "+f"(d[29]), "+f"(d[30]), "+f"(d[31]), "+f"(d[32]), "+f"(d[33]), "+f"(d[34]), "+f"(d[35]), "+f"(d[36]), "+f"(d[37]), "+f"(d[38]), "+f"(d[39]), "+f"(d[40]), "+f"(d[41]), "+f"(d[42]), "+f"(d[43]), "+f"(d[44]), "+f"(d[45]), "+f"(d[46]), "+f"(d[47]), "+f"(d[48]), "+f"(d[49]), "+f"(d[50]), "+f"(d[51]), "+f"(d[52]), "+f"(d[53]), "+f"(d[54]), "+f"(d[55]), "+f"(d[56]), "+f"(d[57]), "+f"(d[58]), "+f"(d[59]), "+f"(d[60]), "+f"(d[61]), "+f"(d[62]), "+f"(d[63])
    : "l"(da), "l"(db), "r"(scale_d), "n"(TB));
}

template<int TB>
__device__ __forceinline__ void wgmma_rs_n128(float (&d)[64], uint32_t a0, uint32_t a1, uint32_t a2, uint32_t a3, uint64_t db, int scale_d) {
  asm volatile("{\n.reg .pred p;\nsetp.ne.b32 p, %69, 0;\n"
    "wgmma.mma_async.sync.aligned.m64n128k16.f32.bf16.bf16 {%0, %1, %2, %3, %4, %5, %6, %7, %8, %9, %10, %11, %12, %13, %14, %15, %16, %17, %18, %19, %20, %21, %22, %23, %24, %25, %26, %27, %28, %29, %30, %31, %32, %33, %34, %35, %36, %37, %38, %39, %40, %41, %42, %43, %44, %45, %46, %47, %48, %49, %50, %51, %52, %53, %54, %55, %56, %57, %58, %59, %60, %61, %62, %63}, {%64, %65, %66, %67}, %68, p, 1, 1, %70;\n}\n"
    : "+f"(d[0]), "+f"(d[1]), "+f"(d[2]), "+f"(d[3]), "+f"(d[4]), "+f"(d[5]), "+f"(d[6]), "+f"(d[7]), "+f"(d[8]), "+f"(d[9]), "+f"(d[10]), "+f"(d[11]), "+f"(d[12]), "+f"(d[13]), "+f"(d[14]), "+f"(d[15]), "+f"(d[16]), "+f"(d[17]), "+f"(d[18]), "+f"(d[19]), "+f"(d[20]), "+f"(d[21]), "+f"(d[22]), "+f"(d[23]), "+f"(d[24]), "+f"(d[25]), "+f"(d[26]), "+f"(d[27]), "+f"(d[28]), "+f"(d[29]), "+f"(d[30]), "+f"(d[31]), "+f"(d[32]), "+f"(d[33]), "+f"(d[34]), "+f"(d[35]), "+f"(d[36]), "+f"(d[37]), "+f"(d[38]), "+f"(d[39]), "+f"(d[40]), "+f"(d[41]), "+f"(d[42]), "+f"(d[43]), "+f"(d[44]), "+f"(d[45]), "+f"(d[46]), "+f"(d[47]), "+f"(d[48]), "+f"(d[49]), "+f"(d[50]), "+f"(d[51]), "+f"(d[52]), "+f"(d[53]), "+f"(d[54]), "+f"(d[55]), "+f"(d[56]), "+f"(d[57]), "+f"(d[58]), "+f"(d[59]), "+f"(d[60]), "+f"(d[61]), "+f"(d[62]), "+f"(d[63])
    : "r"(a0), "r"(a1), "r"(a2), "r"(a3), "l"(db), "r"(scale_d), "n"(TB));
}

template<int TB>
__device__ __forceinline__ void wgmma_rs_n64(float (&d)[32], uint32_t a0, uint32_t a1, uint32_t a2, uint32_t a3, uint64_t db, int scale_d) {
  asm volatile("{\n.reg .pred p;\nsetp.ne.b32 p, %37, 0;\n"
    "wgmma.mma_async.sync.aligned.m64n64k16.f32.bf16.bf16 {%0, %1, %2, %3, %4, %5, %6, %7, %8, %9, %10, %11, %12, %13, %14, %15, %16, %17, %18, %19, %20, %21, %22, %23, %24, %25, %26, %27, %28, %29, %30, %31}, {%32, %33, %34, %35}, %36, p, 1, 1, %38;\n}\n"
    : "+f"(d[0]), "+f"(d[1]), "+f"(d[2]), "+f"(d[3]), "+f"(d[4]), "+f"(d[5]), "+f"(d[6]), "+f"(d[7]), "+f"(d[8]), "+f"(d[9]), "+f"(d[10]), "+f"(d[11]), "+f"(d[12]), "+f"(d[13]), "+f"(d[14]), "+f"(d[15]), "+f"(d[16]), "+f"(d[17]), "+f"(d[18]), "+f"(d[19]), "+f"(d[20]), "+f"(d[21]), "+f"(d[22]), "+f"(d[23]), "+f"(d[24]), "+f"(d[25]), "+f"(d[26]), "+f"(d[27]), "+f"(d[28]), "+f"(d[29]), "+f"(d[30]), "+f"(d[31])
    : "r"(a0), "r"(a1), "r"(a2), "r"(a3), "l"(db), "r"(scale_d), "n"(TB));
}

template<int TB>
__device__ __forceinline__ void wgmma_ss_n64(float (&d)[32], uint64_t da, uint64_t db, int scale_d) {
  asm volatile("{\n.reg .pred p;\nsetp.ne.b32 p, %34, 0;\n"
    "wgmma.mma_async.sync.aligned.m64n64k16.f32.bf16.bf16 {%0, %1, %2, %3, %4, %5, %6, %7, %8, %9, %10, %11, %12, %13, %14, %15, %16, %17, %18, %19, %20, %21, %22, %23, %24, %25, %26, %27, %28, %29, %30, %31}, %32, %33, p, 1, 1, 0, %35;\n}\n"
    : "+f"(d[0]), "+f"(d[1]), "+f"(d[2]), "+f"(d[3]), "+f"(d[4]), "+f"(d[5]), "+f"(d[6]), "+f"(d[7]), "+f"(d[8]), "+f"(d[9]), "+f"(d[10]), "+f"(d[11]), "+f"(d[12]), "+f"(d[13]), "+f"(d[14]), "+f"(d[15]), "+f"(d[16]), "+f"(d[17]), "+f"(d[18]), "+f"(d[19]), "+f"(d[20]), "+f"(d[21]), "+f"(d[22]), "+f"(d[23]), "+f"(d[24]), "+f"(d[25]), "+f"(d[26]), "+f"(d[27]), "+f"(d[28]), "+f"(d[29]), "+f"(d[30]), "+f"(d[31])
    : "l"(da), "l"(db), "r"(scale_d), "n"(TB));
}

namespace mk {

constexpr int SEQ = 2048, DM = 512, NH = 32, DFF = 1792;
constexpr int NTHREADS = 384;

constexpr uint32_t RING_BYTES = 196608;
constexpr uint32_t STG_OFF = RING_BYTES;
constexpr uint32_t BAR_OFF = STG_OFF + 32768;
constexpr uint32_t B_FULLG = BAR_OFF;
constexpr uint32_t B_EMPTYG = B_FULLG + 32;
constexpr uint32_t B_FULLA = B_EMPTYG + 32;
constexpr uint32_t B_EMPTYA = B_FULLA + 48;
constexpr uint32_t B_STF = B_EMPTYA + 48;
constexpr uint32_t B_STE = B_STF + 32;
constexpr uint32_t B_DONE = B_STE + 32;
constexpr uint32_t B_LN = B_DONE + 8;
constexpr uint32_t MISC_OFF = B_LN + 8;
constexpr uint32_t SMEM_BYTES = MISC_OFF + 64 + 1024;

enum { TM_XN = 0, TM_CKV, TM_H, TM_CTX, TM_WUK, TM_WUV, TM_WG, TM_WU, TM_WD, TM_WO, TM_WQ, TM_KVL, TM_XN64, TM_AUXL, TM_X,
       TM_KVS, TM_HS, TM_CTXS, TM_AUXS, TM_OUTS, TM_COUNT };

enum { IT_KV = 0, IT_GU = 1, IT_DN = 2, IT_OP = 3, IT_AT = 4 };
enum { K_PART = 0, K_FIRST = 1, K_SECOND = 2 };
__host__ __device__ inline uint32_t mk_item(int type, int j, int idx, int k0, int nk, int kind, int np) {
  return (uint32_t)type | (j << 3) | (idx << 6) | (k0 << 11) | (nk << 17) | (kind << 24) | (np << 26);
}
constexpr int MAX_ITEMS = 1024;
constexpr int MAX_CL = 72;
constexpr int AUX_G = 6;

struct Params {
  CUtensorMap tm[TM_COUNT];
  const bf16* x;
  uint32_t never;
  uint16_t off[MAX_CL + 8];
  uint32_t items[MAX_ITEMS];
};

constexpr int F_LN = 0;
constexpr int F_KV = 32;
constexpr int F_H = F_KV + 512;
constexpr int F_CTX = F_H + 32;
constexpr int F_G = F_CTX + 512;
constexpr int F_PART = F_G + 32;
constexpr int F_START = F_PART + 64;
constexpr int F_COUNT = F_START + 32;

__device__ __align__(1024) bf16 g_xn[SEQ * DM];
__device__ __align__(1024) bf16 g_kv[SEQ * 8192];
__device__ __align__(1024) bf16 g_h[SEQ * DFF];
__device__ __align__(1024) bf16 g_ctx[SEQ * 4096];
__device__ __align__(1024) bf16 g_aux[7 * SEQ * DM];
__device__ unsigned g_flags[F_COUNT];
__device__ unsigned g_epoch;

__device__ __forceinline__ uint32_t smem_u32(const void* p) { return (uint32_t)__cvta_generic_to_shared(p); }
__device__ __forceinline__ void mbar_init(uint32_t bar, int cnt) {
  asm volatile("mbarrier.init.shared::cta.b64 [%0], %1;" ::"r"(bar), "r"(cnt));
}
__device__ __forceinline__ void mbar_expect_tx(uint32_t bar, uint32_t bytes) {
  asm volatile("mbarrier.arrive.expect_tx.shared::cta.b64 _, [%0], %1;" ::"r"(bar), "r"(bytes) : "memory");
}
__device__ __forceinline__ void mbar_arrive(uint32_t bar) {
  asm volatile("mbarrier.arrive.shared::cta.b64 _, [%0];" ::"r"(bar) : "memory");
}
__device__ __forceinline__ void mbar_arrive_cta(uint32_t bar, uint32_t cta) {
  asm volatile("{\n.reg .b32 ra;\nmapa.shared::cluster.u32 ra, %0, %1;\nmbarrier.arrive.shared::cluster.b64 _, [ra];\n}"
               ::"r"(bar), "r"(cta) : "memory");
}
__device__ __forceinline__ bool mbar_try(uint32_t bar, uint32_t parity) {
  uint32_t ok;
  asm volatile("{\n.reg .pred p;\nmbarrier.try_wait.parity.shared::cta.b64 p, [%1], %2;\nselp.u32 %0, 1, 0, p;\n}"
               : "=r"(ok) : "r"(bar), "r"(parity) : "memory");
  return ok != 0;
}
__device__ __forceinline__ uint32_t clk32() {
  uint32_t t;
  asm volatile("mov.u32 %0, %%clock;" : "=r"(t));
  return t;
}
__device__ __forceinline__ void spin_guard(uint32_t t0) {
  asm volatile("{\n.reg .pred p;\n.reg .s32 d;\nmov.u32 d, %%clock;\nsub.s32 d, d, %0;\nsetp.lt.s32 p, d, 0;\n@p st.global.u32 [%1], %0;\n}"
               ::"r"(t0), "l"(0ull) : "memory");
}
__device__ __forceinline__ void mbar_wait(uint32_t bar, uint32_t parity) {
  if (mbar_try(bar, parity)) return;
  const uint32_t t0 = clk32();
  while (!mbar_try(bar, parity)) spin_guard(t0);
}
#define NAP 100
__device__ __forceinline__ void mbar_wait_nap(uint32_t bar, uint32_t parity) {
  if (mbar_try(bar, parity)) return;
  const uint32_t t0 = clk32();
  do {
    if (NAP) __nanosleep(NAP);
    spin_guard(t0);
  } while (!mbar_try(bar, parity));
}
__device__ __forceinline__ void tma_load_2d(uint32_t dst, const CUtensorMap* m, uint32_t bar, int c0, int c1) {
  asm volatile("cp.async.bulk.tensor.2d.shared::cluster.global.mbarrier::complete_tx::bytes [%0], [%1, {%3, %4}], [%2];"
               ::"r"(dst), "l"(m), "r"(bar), "r"(c0), "r"(c1) : "memory");
}
__device__ __forceinline__ void tma_load_2d_mc(uint32_t dst, const CUtensorMap* m, uint32_t bar, int c0, int c1) {
  asm volatile("cp.async.bulk.tensor.2d.shared::cluster.global.mbarrier::complete_tx::bytes.multicast::cluster [%0], [%1, {%3, %4}], [%2], %5;"
               ::"r"(dst), "l"(m), "r"(bar), "r"(c0), "r"(c1), "h"((uint16_t)3) : "memory");
}
__device__ __forceinline__ void tma_load_3d_mc(uint32_t dst, const CUtensorMap* m, uint32_t bar, int c0, int c1, int c2) {
  asm volatile("cp.async.bulk.tensor.3d.shared::cluster.global.mbarrier::complete_tx::bytes.multicast::cluster [%0], [%1, {%3, %4, %5}], [%2], %6;"
               ::"r"(dst), "l"(m), "r"(bar), "r"(c0), "r"(c1), "r"(c2), "h"((uint16_t)3) : "memory");
}
__device__ __forceinline__ void tma_store_2d(const CUtensorMap* m, uint32_t src, int c0, int c1) {
  asm volatile("cp.async.bulk.tensor.2d.global.shared::cta.bulk_group [%0, {%2, %3}], [%1];"
               ::"l"(m), "r"(src), "r"(c0), "r"(c1) : "memory");
}
__device__ __forceinline__ unsigned ld_acquire(const unsigned* p) {
  unsigned v;
  asm volatile("ld.acquire.gpu.global.u32 %0, [%1];" : "=r"(v) : "l"(p) : "memory");
  return v;
}
__device__ __forceinline__ void red_release(unsigned* p) {
  asm volatile("red.release.gpu.global.add.u32 [%0], 1;" ::"l"(p) : "memory");
}
__device__ __forceinline__ void wait_flag(const unsigned* p, unsigned target) {
  const uint32_t t0 = clk32();
  while ((int)(ld_acquire(p) - target) < 0) {
    __nanosleep(40);
    spin_guard(t0);
  }
}
__device__ __forceinline__ uint64_t mkdesc(uint32_t addr, uint32_t lbo, uint32_t sbo) {
  return (uint64_t)((addr & 0x3FFFF) >> 4) | ((uint64_t)(lbo >> 4) << 16) | ((uint64_t)(sbo >> 4) << 32) | (1ull << 62);
}
#define WG_FENCE() asm volatile("wgmma.fence.sync.aligned;" ::: "memory")
#define WG_COMMIT() asm volatile("wgmma.commit_group.sync.aligned;" ::: "memory")
#define WG_WAIT(n) asm volatile("wgmma.wait_group.sync.aligned %0;" ::"n"(n) : "memory")
template <int N> __device__ __forceinline__ void fence_regs(float (&r)[N]) {
#pragma unroll
  for (int i = 0; i < N; i++) asm volatile("" : "+f"(r[i])::"memory");
}
template <int N> __device__ __forceinline__ void fence_regs(uint32_t (&r)[N]) {
#pragma unroll
  for (int i = 0; i < N; i++) asm volatile("" : "+r"(r[i])::"memory");
}
__device__ __forceinline__ uint32_t pack_bf16(float lo, float hi) {
  uint32_t r;
  asm("cvt.rn.bf16x2.f32 %0, %1, %2;" : "=r"(r) : "f"(hi), "f"(lo));
  return r;
}
__device__ __forceinline__ float round_bf16(float v) { return __bfloat162float(__float2bfloat16_rn(v)); }
__device__ __forceinline__ float ex2(float x) {
  float y;
  asm("ex2.approx.ftz.f32 %0, %1;" : "=f"(y) : "f"(x));
  return y;
}
__device__ __forceinline__ void stsm_x4(uint32_t addr, uint32_t a, uint32_t b, uint32_t c, uint32_t d) {
  asm volatile("stmatrix.sync.aligned.m8n8.x4.shared.b16 [%0], {%1, %2, %3, %4};" ::"r"(addr), "r"(a), "r"(b), "r"(c), "r"(d) : "memory");
}
__device__ __forceinline__ void ldsm_x4(uint32_t addr, uint32_t* r) {
  asm volatile("ldmatrix.sync.aligned.m8n8.x4.shared.b16 {%0, %1, %2, %3}, [%4];"
               : "=r"(r[0]), "=r"(r[1]), "=r"(r[2]), "=r"(r[3]) : "r"(addr) : "memory");
}
__device__ __forceinline__ float tanh_f(float x) {
  float y;
  asm("tanh.approx.f32 %0, %1;" : "=f"(y) : "f"(x));
  return y;
}
__device__ __forceinline__ float bf_lo(uint32_t v) { return __uint_as_float(v << 16); }
__device__ __forceinline__ float bf_hi(uint32_t v) { return __uint_as_float(v & 0xffff0000u); }
__device__ __forceinline__ void bar_sync(int id, int n) { asm volatile("bar.sync %0, %1;" ::"r"(id), "r"(n) : "memory"); }
__device__ __forceinline__ void bar_arrive(int id, int n) { asm volatile("bar.arrive %0, %1;" ::"r"(id), "r"(n) : "memory"); }
__device__ __forceinline__ void cluster_sync() {
  asm volatile("barrier.cluster.arrive.aligned;\nbarrier.cluster.wait.aligned;" ::: "memory");
}
#define TR1(c)
#define TR2(c)

struct Ring {
  uint32_t gs, as;
  uint32_t gph, aph;
  uint32_t mode;
  __device__ __forceinline__ void to_g() {
    if (mode != 0) { mode = 0; gs = (0x032210u >> (as * 4)) & 3; }
  }
  __device__ __forceinline__ void to_a() {
    if (mode != 1) { mode = 1; as = (0x5320u >> (gs * 4)) & 7; }
  }
};

struct Cons {
  uint32_t sb;
  uint32_t lane, wi, w;
  uint32_t never;
  uint32_t stc;
  Ring r;
  __device__ __forceinline__ void release(uint32_t bar) {
    if (lane < 2) mbar_arrive_cta(bar, lane);
  }
  __device__ __forceinline__ void stage_box(const uint32_t* p) {
    uint32_t b = stc & 1;
    mbar_wait(sb + B_STE + (w * 2 + b) * 8, ((stc >> 1) & 1) ^ 1);
    uint32_t row = wi * 16 + ((lane >> 3) & 1) * 8 + (lane & 7);
    uint32_t base = sb + STG_OFF + w * 16384 + b * 8192 + row * 128;
#pragma unroll
    for (int kk = 0; kk < 4; kk++) {
      uint32_t ch = (2 * kk + (lane >> 4)) ^ (lane & 7);
      stsm_x4(base + ch * 16, p[4 * kk], p[4 * kk + 1], p[4 * kk + 2], p[4 * kk + 3]);
    }
    asm volatile("fence.proxy.async.shared::cta;" ::: "memory");
    __syncwarp();
    if (lane == 0) mbar_arrive(sb + B_STF + (w * 2 + b) * 8);
    stc++;
  }
};

__device__ __forceinline__ float gelu_mul(float g, float u) {
  const float z = g * fmaf(g * g, 0.044715f * 0.7978845608028654f, 0.7978845608028654f);
  const float hu = 0.5f * g * u;
  return fmaf(hu, tanh_f(z), hu);
}
__device__ __forceinline__ float silu_f(float d) {
  const float hd = 0.5f * d;
  return fmaf(hd, tanh_f(hd), hd);
}

__device__ __forceinline__ void gemm_item(Cons& c, uint32_t item) {
  const int type = item & 7, nk = (item >> 17) & 127;
  float acc[128];
#pragma unroll
  for (int i = 0; i < 128; i++) acc[i] = 0.f;
  c.r.to_g();
  uint32_t prev = 0;
  for (int ks = 0; ks < nk; ks++) {
    uint32_t s = c.r.gs;
    mbar_wait(c.sb + B_FULLG + s * 8, (c.r.gph >> s) & 1);
    if (ks == 0) TR1(c);
    c.r.gph ^= 1u << s;
    c.r.gs = (s + 1) & 3;
    uint32_t base = c.sb + s * 49152;
    uint64_t da = mkdesc(base + c.w * 8192, 16, 1024);
    uint64_t db = mkdesc(base + 16384, 8192, 1024);
    WG_FENCE();
#pragma unroll
    for (int kk = 0; kk < 4; kk++) wgmma_ss_n256<1>(acc, da + kk * 2, db + kk * 128, 1);
    WG_COMMIT();
    if (ks > 0) {
      WG_WAIT(1);
      c.release(c.sb + B_EMPTYG + prev * 8);
    }
    prev = s;
  }
  WG_WAIT(0);
  fence_regs(acc);
  c.release(c.sb + B_EMPTYG + prev * 8);
  TR2(c);

  uint32_t pk[16];
  if (type == IT_GU) {
#pragma unroll
    for (int b = 0; b < 2; b++) {
#pragma unroll
      for (int i = 0; i < 16; i++)
        pk[i] = pack_bf16(gelu_mul(acc[b * 32 + 2 * i], acc[64 + b * 32 + 2 * i]),
                          gelu_mul(acc[b * 32 + 2 * i + 1], acc[64 + b * 32 + 2 * i + 1]));
      c.stage_box(pk);
    }
  } else {
    const uint32_t kind = (type == IT_KV) ? K_PART : ((item >> 24) & 3);
    const uint32_t np = (kind == K_PART) ? 0 : ((item >> 26) & 7);
    const uint32_t frag = c.w * 8192 + (c.wi * 16 + ((c.lane >> 3) & 1) * 8 + (c.lane & 7)) * 128;
#pragma unroll
    for (int b = 0; b < 4; b++) {
      if (kind != K_PART) {
        uint32_t s = 0, pos = 3;
        auto next_aux = [&](bool first) {
          if (pos == 3) {
            if (!first) c.release(c.sb + B_EMPTYG + s * 8);
            s = c.r.gs;
            mbar_wait(c.sb + B_FULLG + s * 8, (c.r.gph >> s) & 1);
            c.r.gph ^= 1u << s;
            c.r.gs = (s + 1) & 3;
            pos = 0;
          }
          const uint32_t base = c.sb + s * 49152 + pos * 16384 + frag;
#pragma unroll
          for (int kk = 0; kk < 4; kk++) ldsm_x4(base + (((2 * kk + (c.lane >> 4)) ^ (c.lane & 7)) << 4), &pk[4 * kk]);
          pos++;
        };
#pragma unroll 1
        for (uint32_t a = 0; a < np; a++) {
          next_aux(a == 0);
#pragma unroll
          for (int i = 0; i < 16; i++) { acc[b * 32 + 2 * i] += bf_lo(pk[i]); acc[b * 32 + 2 * i + 1] += bf_hi(pk[i]); }
        }
        if (type == IT_DN) {
#pragma unroll
          for (int i = 0; i < 32; i++) acc[b * 32 + i] = silu_f(acc[b * 32 + i]);
        }
        if (kind == K_SECOND) {
          next_aux(np == 0);
#pragma unroll
          for (int i = 0; i < 16; i++) { acc[b * 32 + 2 * i] *= bf_lo(pk[i]); acc[b * 32 + 2 * i + 1] *= bf_hi(pk[i]); }
          next_aux(false);
#pragma unroll
          for (int i = 0; i < 16; i++) { acc[b * 32 + 2 * i] += bf_lo(pk[i]); acc[b * 32 + 2 * i + 1] += bf_hi(pk[i]); }
        }
        if (np != 0 || kind == K_SECOND) { __syncwarp(); c.release(c.sb + B_EMPTYG + s * 8); }
      }
#pragma unroll
      for (int i = 0; i < 16; i++) pk[i] = pack_bf16(acc[b * 32 + 2 * i], acc[b * 32 + 2 * i + 1]);
      c.stage_box(pk);
    }
  }
}

struct Slot { uint32_t s, ph; };
__device__ __forceinline__ Slot take_a(Ring& r) {
  Slot t;
  t.s = r.as;
  t.ph = (r.aph >> t.s) & 1;
  r.aph ^= 1u << t.s;
  r.as = (t.s == 5) ? 0 : t.s + 1;
  return t;
}

__device__ __forceinline__ void qk_issue(float (&S)[64], uint32_t qbase, uint32_t kbase) {
  uint64_t da = mkdesc(qbase, 16, 1024);
  uint64_t db = mkdesc(kbase, 16, 1024);
#pragma unroll
  for (int kk = 0; kk < 8; kk++)
    wgmma_ss_n128<0>(S, da + (kk >> 2) * 512 + (kk & 3) * 2, db + (kk >> 2) * 1024 + (kk & 3) * 2, kk != 0);
}
__device__ __forceinline__ void pv_issue(float (&O)[64], const uint32_t (&P)[32], uint32_t vbase) {
  uint64_t db = mkdesc(vbase, 16384, 1024);
#pragma unroll
  for (int kk = 0; kk < 8; kk++)
    wgmma_rs_n128<1>(O, P[4 * kk], P[4 * kk + 1], P[4 * kk + 2], P[4 * kk + 3], db + kk * 128, 1);
}

__device__ __forceinline__ void row_max(const float (&S)[64], float& x0, float& x1) {
  int i0 = __float_as_int(x0), i1 = __float_as_int(x1);
#pragma unroll
  for (int b = 0; b < 16; b++) {
    i0 = __vimax3_s32(i0, __float_as_int(S[4 * b]), __float_as_int(S[4 * b + 1]));
    i1 = __vimax3_s32(i1, __float_as_int(S[4 * b + 2]), __float_as_int(S[4 * b + 3]));
  }
  if ((i0 | i1) < 0) {
#pragma unroll
    for (int b = 0; b < 16; b++) {
      x0 = fmaxf(x0, fmaxf(S[4 * b], S[4 * b + 1]));
      x1 = fmaxf(x1, fmaxf(S[4 * b + 2], S[4 * b + 3]));
    }
  } else {
    x0 = __int_as_float(i0);
    x1 = __int_as_float(i1);
  }
  x0 = fmaxf(x0, __shfl_xor_sync(0xffffffffu, x0, 1));
  x1 = fmaxf(x1, __shfl_xor_sync(0xffffffffu, x1, 1));
  x0 = fmaxf(x0, __shfl_xor_sync(0xffffffffu, x0, 2));
  x1 = fmaxf(x1, __shfl_xor_sync(0xffffffffu, x1, 2));
}
#define PIN_B 9

__device__ __forceinline__ void attn_item(Cons& c, uint32_t item, uint32_t rank) {
  const int j = (item >> 3) & 7;
  const bool lng = (((item >> 24) & 1) != c.w);
  const uint32_t odd = lng ? (rank ^ 1) : rank;
  const int nblk = 2 * j + (lng ? 2 : 1);
  constexpr float CS = 0.08838834764831845f * 1.4426950408889634f;
  float S[64], O[64];
  uint32_t P[32];
  const uint32_t qbase = c.sb + STG_OFF + c.w * 16384;
  c.r.to_a();
  {
    uint32_t px = 0, pw = 0;
#pragma unroll
    for (int i = 0; i < 64; i++) S[i] = 0.f;
#pragma unroll 1
    for (int ch = 0; ch < 4; ch++) {
      Slot tx = take_a(c.r), tw = take_a(c.r);
      mbar_wait(c.sb + B_FULLA + tx.s * 8, tx.ph);
      mbar_wait(c.sb + B_FULLA + tw.s * 8, tw.ph);
      uint64_t da = mkdesc(c.sb + tx.s * 32768 + c.w * 8192, 16, 1024);
      uint64_t db = mkdesc(c.sb + tw.s * 32768, 16384, 1024);
      WG_FENCE();
#pragma unroll
      for (int kk = 0; kk < 8; kk++) wgmma_ss_n128<1>(S, da + (kk >> 2) * 1024 + (kk & 3) * 2, db + kk * 128, 1);
      WG_COMMIT();
      if (ch > 0) {
        WG_WAIT(1);
        c.release(c.sb + B_EMPTYA + px * 8);
        c.release(c.sb + B_EMPTYA + pw * 8);
      }
      px = tx.s; pw = tw.s;
    }
    mbar_wait(c.sb + B_STE + (c.w * 2 + (c.stc & 1)) * 8, ((c.stc >> 1) & 1) ^ 1);
    mbar_wait(c.sb + B_STE + (c.w * 2 + ((c.stc + 1) & 1)) * 8, (((c.stc + 1) >> 1) & 1) ^ 1);
    WG_WAIT(0);
    fence_regs(S);
    c.release(c.sb + B_EMPTYA + px * 8);
    c.release(c.sb + B_EMPTYA + pw * 8);
    const uint32_t row = c.wi * 16 + ((c.lane >> 3) & 1) * 8 + (c.lane & 7);
#pragma unroll
    for (int kk = 0; kk < 8; kk++) {
      const uint32_t ch = (2 * (kk & 3) + (c.lane >> 4)) ^ (c.lane & 7);
      stsm_x4(qbase + (kk >> 2) * 8192 + row * 128 + ch * 16, pack_bf16(S[8 * kk], S[8 * kk + 1]), pack_bf16(S[8 * kk + 2], S[8 * kk + 3]),
              pack_bf16(S[8 * kk + 4], S[8 * kk + 5]), pack_bf16(S[8 * kk + 6], S[8 * kk + 7]));
    }
    asm volatile("fence.proxy.async.shared::cta;" ::: "memory");
    bar_sync(1 + c.w, 128);
  }
  TR1(c);
  if (!lng) {
    Slot t = take_a(c.r);
    mbar_wait(c.sb + B_FULLA + t.s * 8, t.ph);
    c.release(c.sb + B_EMPTYA + t.s * 8);
  }
  float m0, m1, l0, l1;
  {
    Slot tk = take_a(c.r);
    mbar_wait(c.sb + B_FULLA + tk.s * 8, tk.ph);
    WG_FENCE();
    qk_issue(S, qbase, c.sb + tk.s * 32768);
    WG_COMMIT();
#pragma unroll
    for (int i = 0; i < 64; i++) O[i] = 0.f;
    WG_WAIT(0);
    fence_regs(S);
    c.release(c.sb + B_EMPTYA + tk.s * 8);
    const int r0 = odd * 64 + c.wi * 16 + (c.lane >> 2) - (c.lane & 3) * 2;
#pragma unroll
    for (int b = 0; b < 16; b++) {
      if (b * 8 > r0) S[4 * b] = -INFINITY;
      if (b * 8 + 1 > r0) S[4 * b + 1] = -INFINITY;
      if (b * 8 - 8 > r0) S[4 * b + 2] = -INFINITY;
      if (b * 8 - 7 > r0) S[4 * b + 3] = -INFINITY;
    }
    m0 = -INFINITY; m1 = -INFINITY;
    row_max(S, m0, m1);
    const float n0 = -m0 * CS, n1 = -m1 * CS;
    l0 = 0.f; l1 = 0.f;
#pragma unroll
    for (int b = 0; b < 16; b++) {
      float a0 = ex2(fmaf(S[4 * b], CS, n0)), a1 = ex2(fmaf(S[4 * b + 1], CS, n0));
      float a2 = ex2(fmaf(S[4 * b + 2], CS, n1)), a3 = ex2(fmaf(S[4 * b + 3], CS, n1));
      l0 += a0 + a1; l1 += a2 + a3;
      P[2 * b] = pack_bf16(a0, a1);
      P[2 * b + 1] = pack_bf16(a2, a3);
    }
  }
  if (!lng) {
    Slot t = take_a(c.r);
    mbar_wait(c.sb + B_FULLA + t.s * 8, t.ph);
    c.release(c.sb + B_EMPTYA + t.s * 8);
  }
  Slot tk = take_a(c.r), tv = tk;
  if (nblk > 1) tv = take_a(c.r);
  mbar_wait(c.sb + B_FULLA + tk.s * 8, tk.ph);
  mbar_wait(c.sb + B_FULLA + tv.s * 8, tv.ph);
#pragma unroll 1
  for (int it = 1; it < nblk; it++) {
    fence_regs(P);
    fence_regs(O);
    WG_FENCE();
    qk_issue(S, qbase, c.sb + tk.s * 32768);
    WG_COMMIT();
    pv_issue(O, P, c.sb + tv.s * 32768);
    WG_COMMIT();
    const uint32_t ek = c.sb + B_EMPTYA + tk.s * 8, ev = c.sb + B_EMPTYA + tv.s * 8;
    tk = take_a(c.r);
    tv = tk;
    if (it + 1 < nblk) tv = take_a(c.r);
    WG_WAIT(1);
    fence_regs(S);
    c.release(ek);
    float x0 = m0, x1 = m1;
    row_max(S, x0, x1);
    const float n0 = -x0 * CS, n1 = -x1 * CS;
    const float sc0 = ex2(fmaf(m0, CS, n0)), sc1 = ex2(fmaf(m1, CS, n1));
    m0 = x0; m1 = x1;
    l0 *= sc0; l1 *= sc1;
    bool ok;
#pragma unroll
    for (int b = 0; b < 16; b++) {
      S[4 * b] = ex2(fmaf(S[4 * b], CS, n0));
      S[4 * b + 1] = ex2(fmaf(S[4 * b + 1], CS, n0));
      S[4 * b + 2] = ex2(fmaf(S[4 * b + 2], CS, n1));
      S[4 * b + 3] = ex2(fmaf(S[4 * b + 3], CS, n1));
      l0 += S[4 * b] + S[4 * b + 1];
      l1 += S[4 * b + 2] + S[4 * b + 3];
      if (b == PIN_B) {
        asm volatile("{\n.reg .pred p;\nsetp.eq.u32 p, %0, %1;\n@p st.shared.u32 [%1], 0;\n}"
                     ::"r"(__float_as_uint(S[4 * b + 3])), "r"(c.never) : "memory");
        WG_WAIT(0);
        c.release(ev);
        ok = mbar_try(c.sb + B_FULLA + tk.s * 8, tk.ph) & mbar_try(c.sb + B_FULLA + tv.s * 8, tv.ph);
      }
    }
    fence_regs(O);
    fence_regs(P);
#pragma unroll
    for (int b = 0; b < 16; b++) {
      O[4 * b] *= sc0; O[4 * b + 1] *= sc0; O[4 * b + 2] *= sc1; O[4 * b + 3] *= sc1;
      P[2 * b] = pack_bf16(S[4 * b], S[4 * b + 1]);
      P[2 * b + 1] = pack_bf16(S[4 * b + 2], S[4 * b + 3]);
    }
    if (!ok) {
      mbar_wait(c.sb + B_FULLA + tk.s * 8, tk.ph);
      mbar_wait(c.sb + B_FULLA + tv.s * 8, tv.ph);
    }
  }
  TR2(c);
  {
    fence_regs(P);
    fence_regs(O);
    WG_FENCE();
    pv_issue(O, P, c.sb + tv.s * 32768);
    WG_COMMIT();
    l0 += __shfl_xor_sync(0xffffffffu, l0, 1);
    l1 += __shfl_xor_sync(0xffffffffu, l1, 1);
    l0 += __shfl_xor_sync(0xffffffffu, l0, 2);
    l1 += __shfl_xor_sync(0xffffffffu, l1, 2);
    const float i0 = __fdividef(1.0f, l0), i1 = __fdividef(1.0f, l1);
    WG_WAIT(0);
    fence_regs(O);
    c.release(c.sb + B_EMPTYA + tv.s * 8);
    uint32_t pk[16];
#pragma unroll
    for (int b = 0; b < 2; b++) {
#pragma unroll
      for (int i = 0; i < 8; i++) {
        pk[2 * i] = pack_bf16(O[b * 32 + 4 * i] * i0, O[b * 32 + 4 * i + 1] * i0);
        pk[2 * i + 1] = pack_bf16(O[b * 32 + 4 * i + 2] * i1, O[b * 32 + 4 * i + 3] * i1);
      }
      c.stage_box(pk);
    }
  }
}

struct Prod {
  uint32_t sb;
  Ring r;
  __device__ __forceinline__ uint32_t acquire_g(uint32_t bytes) {
    uint32_t s = r.gs;
    mbar_wait_nap(sb + B_EMPTYG + s * 8, (r.gph >> s) & 1);
    uint32_t a0 = s + (s >> 1);
    mbar_wait_nap(sb + B_EMPTYA + a0 * 8, (r.aph >> a0) & 1);
    mbar_wait_nap(sb + B_EMPTYA + (a0 + 1) * 8, (r.aph >> (a0 + 1)) & 1);
    r.gph ^= 1u << s;
    r.gs = (s + 1) & 3;
    mbar_expect_tx(sb + B_FULLG + s * 8, bytes);
    return s;
  }
  __device__ __forceinline__ uint32_t acquire_a() {
    uint32_t s = r.as;
    mbar_wait_nap(sb + B_EMPTYA + s * 8, (r.aph >> s) & 1);
    uint32_t g0 = (s * 2) / 3, g1 = (s * 2 + 1) / 3;
    mbar_wait_nap(sb + B_EMPTYG + g0 * 8, (r.gph >> g0) & 1);
    mbar_wait_nap(sb + B_EMPTYG + g1 * 8, (r.gph >> g1) & 1);
    r.aph ^= 1u << s;
    r.as = (s == 5) ? 0 : s + 1;
    mbar_expect_tx(sb + B_FULLA + s * 8, 32768);
    return s;
  }
};

__global__ void __cluster_dims__(2, 1, 1) __launch_bounds__(NTHREADS, 1)
mega_kernel(const __grid_constant__ Params p) {
  extern __shared__ uint8_t smem_raw[];
  const uint32_t sb = (smem_u32(smem_raw) + 1023) & ~1023u;
  const uint32_t tid = threadIdx.x, lane = tid & 31;
  const uint32_t warp = __shfl_sync(0xffffffffu, tid >> 5, 0);
  uint32_t rank;
  asm volatile("mov.u32 %0, %%cluster_ctarank;" : "=r"(rank));
  const uint32_t cl = blockIdx.x >> 1;
  const int i_beg = p.off[cl], i_end = p.off[cl + 1];

  unsigned ep1;
  asm volatile("ld.relaxed.gpu.global.u32 %0, [%1];" : "=r"(ep1) : "l"(&g_epoch) : "memory");
  ep1 += 1;

  if (tid == 0) {
    for (int i = 0; i < 4; i++) { mbar_init(sb + B_FULLG + i * 8, 1); mbar_init(sb + B_EMPTYG + i * 8, 16); }
    for (int i = 0; i < 6; i++) { mbar_init(sb + B_FULLA + i * 8, 1); mbar_init(sb + B_EMPTYA + i * 8, 16); }
    for (int i = 0; i < 4; i++) { mbar_init(sb + B_STF + i * 8, 4); mbar_init(sb + B_STE + i * 8, 1); }
    mbar_init(sb + B_DONE, 11);
    mbar_init(sb + B_LN, 8);
    asm volatile("fence.mbarrier_init.release.cluster;" ::: "memory");
  }
  __syncthreads();
  cluster_sync();

  if (warp < 4) {
    asm volatile("setmaxnreg.dec.sync.aligned.u32 40;");
    if (warp == 0) {
      Prod pr;
      pr.sb = sb;
      pr.r.gs = 0; pr.r.as = 0; pr.r.gph = 0xf; pr.r.aph = 0x3f; pr.r.mode = 0;
      for (int n = i_beg; n < i_end; n++) {
        const uint32_t item = p.items[n];
        const int type = item & 7, j = (item >> 3) & 7, idx = (item >> 6) & 31;
        const int k0 = (item >> 11) & 63, nk = (item >> 17) & 127;
        {
          const unsigned* fp = nullptr;
          unsigned cnt = 0;
          const int mt = 2 * j + rank;
          if (type == IT_GU) {
            if (lane == 0) { fp = &g_flags[F_LN + mt]; cnt = 8; }
          } else if (type == IT_DN) {
            if (lane == 0) { fp = &g_flags[F_H + mt]; cnt = 28; }
          } else if (type == IT_OP) {
            const int h0 = k0 >> 1, h1 = (k0 + nk - 1) >> 1;
            if ((int)lane >= h0 && (int)lane <= h1) { fp = &g_flags[F_CTX + mt * 32 + lane]; cnt = 2; }
          } else if (type == IT_AT) {
            if ((int)lane < 2 * j + 2) { fp = &g_flags[F_KV + idx * 16 + lane]; cnt = 2; }
            else if (lane >= 30) { fp = &g_flags[F_LN + 2 * j + (lane - 30)]; cnt = 8; }
          }
          if (fp) wait_flag(fp, ep1 * cnt);
          __syncwarp();
          asm volatile("fence.proxy.async;" ::: "memory");
        }
        if (lane == 0) {
          if (type != IT_AT) {
            pr.r.to_g();
            const CUtensorMap* ta = &p.tm[type == IT_KV ? TM_CKV : type == IT_GU ? TM_XN : type == IT_DN ? TM_H : TM_CTX];
            const CUtensorMap* tb = &p.tm[type == IT_KV ? TM_WUK + rank : type == IT_GU ? TM_WG + rank : type == IT_DN ? TM_WD : TM_WO];
            const int grp = (type <= IT_GU) ? idx * 2 : idx * 4 + rank * 2;
            const int arow = (2 * j + rank) * 128;
            for (int ks = k0; ks < k0 + nk; ks++) {
              uint32_t s = pr.acquire_g(49152);
              uint32_t fb = sb + B_FULLG + s * 8;
              tma_load_2d(sb + s * 49152, ta, fb, ks * 64, arow);
              tma_load_3d_mc(sb + s * 49152 + 16384 + rank * 16384, tb, fb, 0, ks * 64, grp);
            }
            const uint32_t kind = (item >> 24) & 3;
            if (type >= IT_DN && kind != K_PART) {
              const uint32_t np = (item >> 26) & 7, naux = np + (kind == K_SECOND ? 2 : 0);
              const int tile = (2 * j + rank) * 2 + idx;
              if (np) wait_flag(&g_flags[F_PART + (type - IT_DN) * 32 + tile], ep1 * 2 * np);
              if (kind == K_SECOND) wait_flag(&g_flags[F_G + tile], ep1 * 2);
              asm volatile("fence.proxy.async;" ::: "memory");
              for (int b = 0; b < 4; b++) {
                uint32_t s = 0;
                for (uint32_t a = 0, pos = 3; a < naux; a++, pos++) {
                  if (pos == 3) { s = pr.acquire_g(min(naux - a, 3u) * 16384); pos = 0; }
                  const bool isx = (a == np + 1);
                  const int slot = isx ? 0 : (a == np ? AUX_G : (type - IT_DN) * 3 + a);
                  tma_load_2d(sb + s * 49152 + pos * 16384, &p.tm[isx ? TM_X : TM_AUXL], sb + B_FULLG + s * 8,
                              idx * 256 + b * 64, slot * SEQ + arow);
                }
              }
            }
          } else {
            pr.r.to_a();
            const uint32_t sw = (item >> 24) & 1;
            const int rs = j * 256 + rank * 64, rl = j * 256 + (3 - rank) * 64;
            for (int ch = 0; ch < 4; ch++) {
              uint32_t s = pr.acquire_a();
              uint32_t fb = sb + B_FULLA + s * 8;
              tma_load_2d(sb + s * 32768 + sw * 8192, &p.tm[TM_XN64], fb, ch * 128, rs);
              tma_load_2d(sb + s * 32768 + (sw ^ 1) * 8192, &p.tm[TM_XN64], fb, ch * 128, rl);
              tma_load_2d(sb + s * 32768 + 16384 + sw * 8192, &p.tm[TM_XN64], fb, ch * 128 + 64, rs);
              tma_load_2d(sb + s * 32768 + 16384 + (sw ^ 1) * 8192, &p.tm[TM_XN64], fb, ch * 128 + 64, rl);
              s = pr.acquire_a();
              fb = sb + B_FULLA + s * 8;
              tma_load_2d_mc(sb + s * 32768 + rank * 16384, &p.tm[TM_WQ], fb, idx * 128 + rank * 64, ch * 128);
            }
            const int nb = 2 * j + 2;
            const int kc = idx * 256 + rank * 64;
            for (int i = 0; i <= nb; i++) {
              if (i < nb) {
                uint32_t s = pr.acquire_a();
                tma_load_2d_mc(sb + s * 32768 + rank * 16384, &p.tm[TM_KVL], sb + B_FULLA + s * 8, kc, (nb - 1 - i) * 128);
              }
              if (i > 0) {
                uint32_t s = pr.acquire_a();
                tma_load_2d_mc(sb + s * 32768 + rank * 16384, &p.tm[TM_KVL], sb + B_FULLA + s * 8, kc + 128, (nb - i) * 128);
              }
            }
          }
        }
        __syncwarp();
      }
      if (lane == 0) mbar_arrive(sb + B_DONE);
    } else {
      if (warp == 3 && lane == 0) red_release(&g_flags[F_START]);
      if (warp < 3) {
        if (lane == 0) {
          const uint32_t w = warp - 1;
          uint32_t stc = 0;
          for (int n = i_beg; n < i_end; n++) {
            const uint32_t item = p.items[n];
            const int type = item & 7, j = (item >> 3) & 7, idx = (item >> 6) & 31;
            const int mt = 2 * j + rank;
            int row = mt * 128 + w * 64, nbox = 4, col = idx * 256, tmi;
            unsigned* fp = nullptr;
            if (type == IT_KV) { tmi = TM_KVS; fp = &g_flags[F_KV + idx * 16 + mt]; }
            else if (type == IT_GU) { tmi = TM_HS; nbox = 2; col = idx * 128; fp = &g_flags[F_H + mt]; }
            else if (type == IT_AT) {
              const int g = (((item >> 24) & 1) != w) ? 3 - rank : rank;
              row = j * 256 + g * 64;
              tmi = TM_CTXS; nbox = 2; col = idx * 128; fp = &g_flags[F_CTX + (2 * j + (g >> 1)) * 32 + idx];
            } else {
              const uint32_t kind = (item >> 24) & 3;
              tmi = TM_AUXS;
              if (kind == K_PART) { row += ((type - IT_DN) * 3 + ((item >> 26) & 7)) * SEQ; fp = &g_flags[F_PART + (type - IT_DN) * 32 + mt * 2 + idx]; }
              else if (kind == K_FIRST) { row += AUX_G * SEQ; fp = &g_flags[F_G + mt * 2 + idx]; }
              else tmi = TM_OUTS;
            }
            for (int b = 0; b < nbox; b++) {
              const uint32_t bb = stc & 1;
              mbar_wait_nap(sb + B_STF + (w * 2 + bb) * 8, (stc >> 1) & 1);
              tma_store_2d(&p.tm[tmi], sb + STG_OFF + w * 16384 + bb * 8192, col + b * 64, row);
              asm volatile("cp.async.bulk.commit_group;" ::: "memory");
              asm volatile("cp.async.bulk.wait_group.read 0;" ::: "memory");
              mbar_arrive(sb + B_STE + (w * 2 + bb) * 8);
              stc++;
            }
            asm volatile("cp.async.bulk.wait_group 0;" ::: "memory");
            if (fp) { __threadfence(); red_release(fp); }
          }
          mbar_arrive(sb + B_DONE);
        }
      } else if (lane == 0) {
        mbar_wait(sb + B_LN, 0);
        asm volatile("fence.proxy.async;" ::: "memory");
        __threadfence();
        for (int rb = blockIdx.x; rb < 128; rb += gridDim.x) red_release(&g_flags[F_LN + (rb >> 3)]);
        if (blockIdx.x == 0) {
          wait_flag(&g_flags[F_START], ep1 * gridDim.x);
          asm volatile("st.relaxed.gpu.global.u32 [%0], %1;" ::"l"(&g_epoch), "r"(ep1) : "memory");
        }
        const uint32_t t0 = clk32();
        while (!mbar_try(sb + B_DONE, 0)) { __nanosleep(500); spin_guard(t0); }
      }
      __syncwarp();
    }
    cluster_sync();
  } else {
    asm volatile("setmaxnreg.inc.sync.aligned.u32 232;");
    Cons c;
    c.sb = sb; c.lane = lane; c.wi = warp & 3; c.w = (warp >> 2) - 1; c.stc = 0;
    c.r.gs = 0; c.r.as = 0; c.r.gph = 0; c.r.aph = 0; c.r.mode = 0;
    c.never = p.never;
    for (int rb = blockIdx.x; rb < 128; rb += gridDim.x) {
      const int row = rb * 16 + (warp - 4) * 2;
      const uint4* src = (const uint4*)(p.x + row * DM) + lane;
      uint4 v[4];
#pragma unroll
      for (int i = 0; i < 4; i++) v[i] = __ldg(src + i * 32);
#pragma unroll
      for (int rr = 0; rr < 2; rr++) {
        uint32_t u[8] = {v[2 * rr].x, v[2 * rr].y, v[2 * rr].z, v[2 * rr].w, v[2 * rr + 1].x, v[2 * rr + 1].y, v[2 * rr + 1].z, v[2 * rr + 1].w};
        float sum = 0.f;
#pragma unroll
        for (int i = 0; i < 8; i++) sum += bf_lo(u[i]) + bf_hi(u[i]);
#pragma unroll
        for (int o = 16; o; o >>= 1) sum += __shfl_xor_sync(0xffffffffu, sum, o);
        const float mean = sum * (1.0f / DM);
        float vs = 0.f;
#pragma unroll
        for (int i = 0; i < 8; i++) {
          const float d0 = bf_lo(u[i]) - mean, d1 = bf_hi(u[i]) - mean;
          vs = fmaf(d0, d0, fmaf(d1, d1, vs));
        }
#pragma unroll
        for (int o = 16; o; o >>= 1) vs += __shfl_xor_sync(0xffffffffu, vs, o);
        const float mb = round_bf16(mean);
        const float rden = 1.0f / round_bf16(sqrtf(round_bf16(round_bf16(vs * (1.0f / DM)) + 1e-5f)));
#pragma unroll
        for (int i = 0; i < 8; i++) {
          const uint32_t d = pack_bf16(bf_lo(u[i]) - mb, bf_hi(u[i]) - mb);
          u[i] = pack_bf16(bf_lo(d) * rden, bf_hi(d) * rden);
        }
        uint4* dst = (uint4*)(g_xn + (row + rr) * DM) + lane;
        dst[0] = make_uint4(u[0], u[1], u[2], u[3]);
        dst[32] = make_uint4(u[4], u[5], u[6], u[7]);
      }
    }
    __syncwarp();
    if (lane == 0) mbar_arrive(sb + B_LN);
    for (int n = i_beg; n < i_end; n++) {
      const uint32_t item = p.items[n];
      if ((item & 7) == IT_AT) attn_item(c, item, rank);
      else gemm_item(c, item);
    }
    if (lane == 0) mbar_arrive(sb + B_DONE);
    cluster_sync();
  }
}

typedef CUresult (*EncFn)(CUtensorMap*, CUtensorMapDataType, cuuint32_t, void*, const cuuint64_t*, const cuuint64_t*,
                          const cuuint32_t*, const cuuint32_t*, CUtensorMapInterleave, CUtensorMapSwizzle,
                          CUtensorMapL2promotion, CUtensorMapFloatOOBfill);

static void enc2d(EncFn enc, CUtensorMap* m, const void* ptr, uint64_t cols, uint64_t rows, uint32_t bc, uint32_t br) {
  cuuint64_t gd[2] = {cols, rows};
  cuuint64_t gs[1] = {cols * 2};
  cuuint32_t bd[2] = {bc, br}, es[2] = {1, 1};
  enc(m, CU_TENSOR_MAP_DATA_TYPE_BFLOAT16, 2, (void*)ptr, gd, gs, bd, es, CU_TENSOR_MAP_INTERLEAVE_NONE,
      CU_TENSOR_MAP_SWIZZLE_128B, CU_TENSOR_MAP_L2_PROMOTION_L2_256B, CU_TENSOR_MAP_FLOAT_OOB_FILL_NONE);
}
static void enc3d(EncFn enc, CUtensorMap* m, const void* ptr, uint64_t cols, uint64_t rows) {
  cuuint64_t gd[3] = {64, rows, cols / 64};
  cuuint64_t gs[2] = {cols * 2, 128};
  cuuint32_t bd[3] = {64, 64, 2}, es[3] = {1, 1, 1};
  enc(m, CU_TENSOR_MAP_DATA_TYPE_BFLOAT16, 3, (void*)ptr, gd, gs, bd, es, CU_TENSOR_MAP_INTERLEAVE_NONE,
      CU_TENSOR_MAP_SWIZZLE_128B, CU_TENSOR_MAP_L2_PROMOTION_L2_256B, CU_TENSOR_MAP_FLOAT_OOB_FILL_NONE);
}

struct SItem { int type, j, idx, k0, nk, kind, np; float cost, prio, done; int assigned; };
struct SchedCfg {
  int ops[8], dns[8];
  float c_kv, c_gu, c_at0, c_atb, c_ks, c_epi, lat;
  float b_gu, b_dn, b_op, b_h;
};
static SchedCfg g_cfg = {{4, 4, 2, 2, 2, 1, 1, 1}, {1, 1, 1, 1, 1, 1, 1, 1}, 5.6f, 5.8f, 6.5f, 1.45f, 0.63f, 0.8f, 2.0f,
                         0.f, 0.f, 0.f, 0.f};

static float build_schedule(Params& P, int ncl) {
  static SItem it[MAX_ITEMS];
  const SchedCfg& C = g_cfg;
  int n = 0;
  auto add = [&](int type, int j, int idx, int k0, int nk, float cost, float prio) {
    it[n].type = type; it[n].j = j; it[n].idx = idx; it[n].k0 = k0; it[n].nk = nk; it[n].kind = 0; it[n].np = 0;
    it[n].cost = cost; it[n].prio = prio; it[n].done = -1; it[n].assigned = 0; n++;
  };
  float opc[8], dnc[8], atp[8], atmax = 0;
  for (int j = 0; j < 8; j++) {
    opc[j] = (64 / C.ops[j]) * C.c_ks + C.c_epi;
    dnc[j] = (28 / C.dns[j]) * C.c_ks + C.c_epi;
    atp[j] = C.c_at0 + 2 * j * C.c_atb + opc[j] + C.lat;
    if (atp[j] > atmax) atmax = atp[j];
  }
  const int kv0 = n;
  for (int h = 0; h < 32; h++) for (int j = 0; j < 8; j++) add(IT_KV, j, h, 0, 8, C.c_kv, C.c_kv + C.lat + atmax - C.b_h * h);
  const int gu0 = n;
  for (int j = 0; j < 8; j++) for (int f = 0; f < 14; f++) add(IT_GU, j, f, 0, 8, C.c_gu, C.c_gu + C.lat + dnc[j] + C.b_gu - 0.01f * j);
  const int at0 = n;
  for (int j = 0; j < 8; j++) for (int h = 0; h < 32; h++) add(IT_AT, j, h, 0, 0, C.c_at0 + 2 * j * C.c_atb, atp[j] - C.b_h * h);
  for (int j = 0; j < 8; j++) for (int s = 0; s < C.dns[j]; s++) for (int c = 0; c < 2; c++)
    add(IT_DN, j, c, s * (28 / C.dns[j]), 28 / C.dns[j], dnc[j], dnc[j] + C.b_dn);
  for (int j = 0; j < 8; j++) for (int s = 0; s < C.ops[j]; s++) for (int c = 0; c < 2; c++)
    add(IT_OP, j, c, s * (64 / C.ops[j]), 64 / C.ops[j], opc[j], opc[j] + C.b_op);
  auto ready = [&](int i) -> float {
    float t = 0;
    auto dep = [&](int d) { if (t >= 0) { if (!it[d].assigned) t = -1; else if (it[d].done + C.lat > t) t = it[d].done + C.lat; } };
    const SItem& a = it[i];
    if (a.type == IT_GU) t = 5.0f;
    else if (a.type == IT_DN) { for (int f = 0; f < 14; f++) dep(gu0 + a.j * 14 + f); }
    else if (a.type == IT_AT) { for (int j = 0; j <= a.j; j++) dep(kv0 + a.idx * 8 + j); }
    else if (a.type == IT_OP) { for (int h = a.k0 / 2; h <= (a.k0 + a.nk - 1) / 2; h++) dep(at0 + a.j * 32 + h); }
    return t;
  };
  static int list[MAX_CL][64];
  int cnt[MAX_CL], par[MAX_CL];
  float tfree[MAX_CL];
  int parts[2][16];
  float pdone[2][16];
  float fdone[16];
  for (int i = 0; i < 16; i++) { parts[0][i] = parts[1][i] = 0; pdone[0][i] = pdone[1][i] = 0; fdone[i] = -1; }
  for (int c = 0; c < ncl; c++) { cnt[c] = 0; tfree[c] = 1.5f; par[c] = 0; }
  float span = 0;
  for (int left = n; left > 0; left--) {
    int c = 0;
    for (int k = 1; k < ncl; k++) if (tfree[k] < tfree[c]) c = k;
    int best = -1, bw = -1;
    float bt = 1e30f;
    for (int i = 0; i < n; i++) {
      if (it[i].assigned) continue;
      const float r = ready(i);
      if (r < 0) continue;
      if (r <= tfree[c]) { if (best < 0 || it[i].prio > it[best].prio) best = i; }
      else if (r < bt) { bt = r; bw = i; }
    }
    if (best >= 0) bt = tfree[c]; else best = bw;
    SItem& a = it[best];
    a.assigned = 1;
    a.done = bt + a.cost;
    if (a.type == IT_DN || a.type == IT_OP) {
      const int t = a.type - IT_DN, tile = a.j * 2 + a.idx, ns = t ? C.ops[a.j] : C.dns[a.j];
      a.np = parts[t][tile]++;
      if (a.np + 1 < ns) {
        a.kind = K_PART;
        if (a.done > pdone[t][tile]) pdone[t][tile] = a.done;
      } else {
        float e = a.np ? pdone[t][tile] : 0;
        a.kind = fdone[tile] < 0 ? K_FIRST : K_SECOND;
        if (a.kind == K_SECOND && fdone[tile] > e) e = fdone[tile];
        if (e > 0 && e + C.lat + C.c_epi > a.done) a.done = e + C.lat + C.c_epi;
        fdone[tile] = a.done;
      }
    }
    tfree[c] = a.done;
    if (a.done > span) span = a.done;
    list[c][cnt[c]++] = best;
  }
  int o = 0;
  for (int c = 0; c < ncl; c++) {
    P.off[c] = (uint16_t)o;
    for (int k = 0; k < cnt[c]; k++) {
      const SItem& a = it[list[c][k]];
      int kind = a.kind;
      if (a.type == IT_AT) { kind = par[c]; par[c] ^= 1; }
      P.items[o++] = mk_item(a.type, a.j, a.idx, a.k0, a.nk, kind, a.np);
    }
  }
  P.off[ncl] = (uint16_t)o;
  return span;
}

}

extern "C" void kernel_launch(void* const* d_in, const int* in_sizes, int n_in, void* d_out, int out_size) {
  using namespace mk;
  static Params P;
  static int ncl = 0;
  static const void* cached[11];
  bool same = ncl > 0 && cached[10] == d_out;
  for (int i = 0; i < 10 && same; i++) same = cached[i] == d_in[i];
  if (!same) {
    void* fn = nullptr;
    cudaDriverEntryPointQueryResult qr;
    cudaGetDriverEntryPoint("cuTensorMapEncodeTiled", &fn, cudaEnableDefault, &qr);
    EncFn enc = (EncFn)fn;
    void *xn, *kv, *h, *ctx, *aux;
    cudaGetSymbolAddress(&xn, g_xn);
    cudaGetSymbolAddress(&kv, g_kv);
    cudaGetSymbolAddress(&h, g_h);
    cudaGetSymbolAddress(&ctx, g_ctx);
    cudaGetSymbolAddress(&aux, g_aux);
    enc2d(enc, &P.tm[TM_XN], xn, 512, SEQ, 64, 128);
    enc2d(enc, &P.tm[TM_CKV], d_in[1], 512, SEQ, 64, 128);
    enc2d(enc, &P.tm[TM_H], h, DFF, SEQ, 64, 128);
    enc2d(enc, &P.tm[TM_CTX], ctx, 4096, SEQ, 64, 128);
    enc3d(enc, &P.tm[TM_WUK], d_in[3], 4096, 512);
    enc3d(enc, &P.tm[TM_WUV], d_in[4], 4096, 512);
    enc3d(enc, &P.tm[TM_WG], d_in[7], DFF, 512);
    enc3d(enc, &P.tm[TM_WU], d_in[8], DFF, 512);
    enc3d(enc, &P.tm[TM_WD], d_in[9], 512, DFF);
    enc3d(enc, &P.tm[TM_WO], d_in[5], 512, 4096);
    enc2d(enc, &P.tm[TM_WQ], d_in[2], 4096, 512, 64, 128);
    enc2d(enc, &P.tm[TM_KVL], kv, 8192, SEQ, 64, 128);
    enc2d(enc, &P.tm[TM_KVS], kv, 8192, SEQ, 64, 64);
    enc2d(enc, &P.tm[TM_HS], h, DFF, SEQ, 64, 64);
    enc2d(enc, &P.tm[TM_CTXS], ctx, 4096, SEQ, 64, 64);
    enc2d(enc, &P.tm[TM_AUXS], aux, 512, 7 * SEQ, 64, 64);
    enc2d(enc, &P.tm[TM_AUXL], aux, 512, 7 * SEQ, 64, 128);
    enc2d(enc, &P.tm[TM_XN64], xn, 512, SEQ, 64, 64);
    enc2d(enc, &P.tm[TM_X], d_in[0], 512, SEQ, 64, 128);
    enc2d(enc, &P.tm[TM_OUTS], d_out, 512, SEQ, 64, 64);
    P.x = (const bf16*)d_in[0];
    P.never = 0x80000004u;
    cudaFuncSetAttribute(mega_kernel, cudaFuncAttributeMaxDynamicSharedMemorySize, SMEM_BYTES);
    if (ncl == 0) {
      cudaLaunchConfig_t cfg = {};
      cfg.gridDim = dim3(132); cfg.blockDim = dim3(NTHREADS); cfg.dynamicSmemBytes = SMEM_BYTES;
      cudaLaunchAttribute at[1];
      at[0].id = cudaLaunchAttributeClusterDimension;
      at[0].val.clusterDim.x = 2; at[0].val.clusterDim.y = 1; at[0].val.clusterDim.z = 1;
      cfg.attrs = at; cfg.numAttrs = 1;
      int nc = 0;
      if (cudaOccupancyMaxActiveClusters(&nc, mega_kernel, &cfg) != cudaSuccess || nc < 1) { nc = 66; (void)cudaGetLastError(); }
      if (nc > MAX_CL) nc = MAX_CL;
      if (nc < 16) nc = 16;
      ncl = nc;
      build_schedule(P, ncl);
    }
    for (int i = 0; i < 10; i++) cached[i] = d_in[i];
    cached[10] = d_out;
  }
  mega_kernel<<<ncl * 2, NTHREADS, SMEM_BYTES>>>(P);
}
```

```cpp
#include <cuda_runtime.h>
#include <cuda_bf16.h>
#include <cuda.h>
#include <stdint.h>
#include <string.h>

typedef __nv_bfloat16 bf16;

template<int TB>
__device__ __forceinline__ void wgmma_ss_n256(float (&d)[128], uint64_t da, uint64_t db, int scale_d) {
  asm volatile("{\n.reg .pred p;\nsetp.ne.b32 p, %130, 0;\n"
    "wgmma.mma_async.sync.aligned.m64n256k16.f32.bf16.bf16 {%0, %1, %2, %3, %4, %5, %6, %7, %8, %9, %10, %11, %12, %13, %14, %15, %16, %17, %18, %19, %20, %21, %22, %23, %24, %25, %26, %27, %28, %29, %30, %31, %32, %33, %34, %35, %36, %37, %38, %39, %40, %41, %42, %43, %44, %45, %46, %47, %48, %49, %50, %51, %52, %53, %54, %55, %56, %57, %58, %59, %60, %61, %62, %63, %64, %65, %66, %67, %68, %69, %70, %71, %72, %73, %74, %75, %76, %77, %78, %79, %80, %81, %82, %83, %84, %85, %86, %87, %88, %89, %90, %91, %92, %93, %94, %95, %96, %97, %98, %99, %100, %101, %102, %103, %104, %105, %106, %107, %108, %109, %110, %111, %112, %113, %114, %115, %116, %117, %118, %119, %120, %121, %122, %123, %124, %125, %126, %127}, %128, %129, p, 1, 1, 0, %131;\n}\n"
    : "+f"(d[0]), "+f"(d[1]), "+f"(d[2]), "+f"(d[3]), "+f"(d[4]), "+f"(d[5]), "+f"(d[6]), "+f"(d[7]), "+f"(d[8]), "+f"(d[9]), "+f"(d[10]), "+f"(d[11]), "+f"(d[12]), "+f"(d[13]), "+f"(d[14]), "+f"(d[15]), "+f"(d[16]), "+f"(d[17]), "+f"(d[18]), "+f"(d[19]), "+f"(d[20]), "+f"(d[21]), "+f"(d[22]), "+f"(d[23]), "+f"(d[24]), "+f"(d[25]), "+f"(d[26]), "+f"(d[27]), "+f"(d[28]), "+f"(d[29]), "+f"(d[30]), "+f"(d[31]), "+f"(d[32]), "+f"(d[33]), "+f"(d[34]), "+f"(d[35]), "+f"(d[36]), "+f"(d[37]), "+f"(d[38]), "+f"(d[39]), "+f"(d[40]), "+f"(d[41]), "+f"(d[42]), "+f"(d[43]), "+f"(d[44]), "+f"(d[45]), "+f"(d[46]), "+f"(d[47]), "+f"(d[48]), "+f"(d[49]), "+f"(d[50]), "+f"(d[51]), "+f"(d[52]), "+f"(d[53]), "+f"(d[54]), "+f"(d[55]), "+f"(d[56]), "+f"(d[57]), "+f"(d[58]), "+f"(d[59]), "+f"(d[60]), "+f"(d[61]), "+f"(d[62]), "+f"(d[63]), "+f"(d[64]), "+f"(d[65]), "+f"(d[66]), "+f"(d[67]), "+f"(d[68]), "+f"(d[69]), "+f"(d[70]), "+f"(d[71]), "+f"(d[72]), "+f"(d[73]), "+f"(d[74]), "+f"(d[75]), "+f"(d[76]), "+f"(d[77]), "+f"(d[78]), "+f"(d[79]), "+f"(d[80]), "+f"(d[81]), "+f"(d[82]), "+f"(d[83]), "+f"(d[84]), "+f"(d[85]), "+f"(d[86]), "+f"(d[87]), "+f"(d[88]), "+f"(d[89]), "+f"(d[90]), "+f"(d[91]), "+f"(d[92]), "+f"(d[93]), "+f"(d[94]), "+f"(d[95]), "+f"(d[96]), "+f"(d[97]), "+f"(d[98]), "+f"(d[99]), "+f"(d[100]), "+f"(d[101]), "+f"(d[102]), "+f"(d[103]), "+f"(d[104]), "+f"(d[105]), "+f"(d[106]), "+f"(d[107]), "+f"(d[108]), "+f"(d[109]), "+f"(d[110]), "+f"(d[111]), "+f"(d[112]), "+f"(d[113]), "+f"(d[114]), "+f"(d[115]), "+f"(d[116]), "+f"(d[117]), "+f"(d[118]), "+f"(d[119]), "+f"(d[120]), "+f"(d[121]), "+f"(d[122]), "+f"(d[123]), "+f"(d[124]), "+f"(d[125]), "+f"(d[126]), "+f"(d[127])
    : "l"(da), "l"(db), "r"(scale_d), "n"(TB));
}

template<int TB>
__device__ __forceinline__ void wgmma_ss_n128(float (&d)[64], uint64_t da, uint64_t db, int scale_d) {
  asm volatile("{\n.reg .pred p;\nsetp.ne.b32 p, %66, 0;\n"
    "wgmma.mma_async.sync.aligned.m64n128k16.f32.bf16.bf16 {%0, %1, %2, %3, %4, %5, %6, %7, %8, %9, %10, %11, %12, %13, %14, %15, %16, %17, %18, %19, %20, %21, %22, %23, %24, %25, %26, %27, %28, %29, %30, %31, %32, %33, %34, %35, %36, %37, %38, %39, %40, %41, %42, %43, %44, %45, %46, %47, %48, %49, %50, %51, %52, %53, %54, %55, %56, %57, %58, %59, %60, %61, %62, %63}, %64, %65, p, 1, 1, 0, %67;\n}\n"
    : "+f"(d[0]), "+f"(d[1]), "+f"(d[2]), "+f"(d[3]), "+f"(d[4]), "+f"(d[5]), "+f"(d[6]), "+f"(d[7]), "+f"(d[8]), "+f"(d[9]), "+f"(d[10]), "+f"(d[11]), "+f"(d[12]), "+f"(d[13]), "+f"(d[14]), "+f"(d[15]), "+f"(d[16]), "+f"(d[17]), "+f"(d[18]), "+f"(d[19]), "+f"(d[20]), "+f"(d[21]), "+f"(d[22]), "+f"(d[23]), "+f"(d[24]), "+f"(d[25]), "+f"(d[26]), "+f"(d[27]), "+f"(d[28]), "+f"(d[29]), "+f"(d[30]), "+f"(d[31]), "+f"(d[32]), "+f"(d[33]), "+f"(d[34]), "+f"(d[35]), "+f"(d[36]), "+f"(d[37]), "+f"(d[38]), "+f"(d[39]), "+f"(d[40]), "+f"(d[41]), "+f"(d[42]), "+f"(d[43]), "+f"(d[44]), "+f"(d[45]), "+f"(d[46]), "+f"(d[47]), "+f"(d[48]), "+f"(d[49]), "+f"(d[50]), "+f"(d[51]), "+f"(d[52]), "+f"(d[53]), "+f"(d[54]), "+f"(d[55]), "+f"(d[56]), "+f"(d[57]), "+f"(d[58]), "+f"(d[59]), "+f"(d[60]), "+f"(d[61]), "+f"(d[62]), "+f"(d[63])
    : "l"(da), "l"(db), "r"(scale_d), "n"(TB));
}

template<int TB>
__device__ __forceinline__ void wgmma_rs_n128(float (&d)[64], uint32_t a0, uint32_t a1, uint32_t a2, uint32_t a3, uint64_t db, int scale_d) {
  asm volatile("{\n.reg .pred p;\nsetp.ne.b32 p, %69, 0;\n"
    "wgmma.mma_async.sync.aligned.m64n128k16.f32.bf16.bf16 {%0, %1, %2, %3, %4, %5, %6, %7, %8, %9, %10, %11, %12, %13, %14, %15, %16, %17, %18, %19, %20, %21, %22, %23, %24, %25, %26, %27, %28, %29, %30, %31, %32, %33, %34, %35, %36, %37, %38, %39, %40, %41, %42, %43, %44, %45, %46, %47, %48, %49, %50, %51, %52, %53, %54, %55, %56, %57, %58, %59, %60, %61, %62, %63}, {%64, %65, %66, %67}, %68, p, 1, 1, %70;\n}\n"
    : "+f"(d[0]), "+f"(d[1]), "+f"(d[2]), "+f"(d[3]), "+f"(d[4]), "+f"(d[5]), "+f"(d[6]), "+f"(d[7]), "+f"(d[8]), "+f"(d[9]), "+f"(d[10]), "+f"(d[11]), "+f"(d[12]), "+f"(d[13]), "+f"(d[14]), "+f"(d[15]), "+f"(d[16]), "+f"(d[17]), "+f"(d[18]), "+f"(d[19]), "+f"(d[20]), "+f"(d[21]), "+f"(d[22]), "+f"(d[23]), "+f"(d[24]), "+f"(d[25]), "+f"(d[26]), "+f"(d[27]), "+f"(d[28]), "+f"(d[29]), "+f"(d[30]), "+f"(d[31]), "+f"(d[32]), "+f"(d[33]), "+f"(d[34]), "+f"(d[35]), "+f"(d[36]), "+f"(d[37]), "+f"(d[38]), "+f"(d[39]), "+f"(d[40]), "+f"(d[41]), "+f"(d[42]), "+f"(d[43]), "+f"(d[44]), "+f"(d[45]), "+f"(d[46]), "+f"(d[47]), "+f"(d[48]), "+f"(d[49]), "+f"(d[50]), "+f"(d[51]), "+f"(d[52]), "+f"(d[53]), "+f"(d[54]), "+f"(d[55]), "+f"(d[56]), "+f"(d[57]), "+f"(d[58]), "+f"(d[59]), "+f"(d[60]), "+f"(d[61]), "+f"(d[62]), "+f"(d[63])
    : "r"(a0), "r"(a1), "r"(a2), "r"(a3), "l"(db), "r"(scale_d), "n"(TB));
}

template<int TB>
__device__ __forceinline__ void wgmma_rs_n64(float (&d)[32], uint32_t a0, uint32_t a1, uint32_t a2, uint32_t a3, uint64_t db, int scale_d) {
  asm volatile("{\n.reg .pred p;\nsetp.ne.b32 p, %37, 0;\n"
    "wgmma.mma_async.sync.aligned.m64n64k16.f32.bf16.bf16 {%0, %1, %2, %3, %4, %5, %6, %7, %8, %9, %10, %11, %12, %13, %14, %15, %16, %17, %18, %19, %20, %21, %22, %23, %24, %25, %26, %27, %28, %29, %30, %31}, {%32, %33, %34, %35}, %36, p, 1, 1, %38;\n}\n"
    : "+f"(d[0]), "+f"(d[1]), "+f"(d[2]), "+f"(d[3]), "+f"(d[4]), "+f"(d[5]), "+f"(d[6]), "+f"(d[7]), "+f"(d[8]), "+f"(d[9]), "+f"(d[10]), "+f"(d[11]), "+f"(d[12]), "+f"(d[13]), "+f"(d[14]), "+f"(d[15]), "+f"(d[16]), "+f"(d[17]), "+f"(d[18]), "+f"(d[19]), "+f"(d[20]), "+f"(d[21]), "+f"(d[22]), "+f"(d[23]), "+f"(d[24]), "+f"(d[25]), "+f"(d[26]), "+f"(d[27]), "+f"(d[28]), "+f"(d[29]), "+f"(d[30]), "+f"(d[31])
    : "r"(a0), "r"(a1), "r"(a2), "r"(a3), "l"(db), "r"(scale_d), "n"(TB));
}

template<int TB>
__device__ __forceinline__ void wgmma_ss_n64(float (&d)[32], uint64_t da, uint64_t db, int scale_d) {
  asm volatile("{\n.reg .pred p;\nsetp.ne.b32 p, %34, 0;\n"
    "wgmma.mma_async.sync.aligned.m64n64k16.f32.bf16.bf16 {%0, %1, %2, %3, %4, %5, %6, %7, %8, %9, %10, %11, %12, %13, %14, %15, %16, %17, %18, %19, %20, %21, %22, %23, %24, %25, %26, %27, %28, %29, %30, %31}, %32, %33, p, 1, 1, 0, %35;\n}\n"
    : "+f"(d[0]), "+f"(d[1]), "+f"(d[2]), "+f"(d[3]), "+f"(d[4]), "+f"(d[5]), "+f"(d[6]), "+f"(d[7]), "+f"(d[8]), "+f"(d[9]), "+f"(d[10]), "+f"(d[11]), "+f"(d[12]), "+f"(d[13]), "+f"(d[14]), "+f"(d[15]), "+f"(d[16]), "+f"(d[17]), "+f"(d[18]), "+f"(d[19]), "+f"(d[20]), "+f"(d[21]), "+f"(d[22]), "+f"(d[23]), "+f"(d[24]), "+f"(d[25]), "+f"(d[26]), "+f"(d[27]), "+f"(d[28]), "+f"(d[29]), "+f"(d[30]), "+f"(d[31])
    : "l"(da), "l"(db), "r"(scale_d), "n"(TB));
}

namespace mk {

constexpr int SEQ = 2048, DM = 512, NH = 32, DFF = 1792;
constexpr int NTHREADS = 384;

constexpr uint32_t RING_BYTES = 196608;
constexpr uint32_t STG_OFF = RING_BYTES;
constexpr uint32_t BAR_OFF = STG_OFF + 32768;
constexpr uint32_t B_FULLG = BAR_OFF;
constexpr uint32_t B_FULLA = B_FULLG + 32;
constexpr uint32_t B_EMPTYG = B_FULLA + 48;
constexpr uint32_t B_EMPTYA = B_EMPTYG + 32;
constexpr uint32_t B_STF = B_EMPTYA + 48;
constexpr uint32_t B_ST2 = B_STF + 16;
constexpr uint32_t B_STE = B_ST2 + 16;
constexpr uint32_t B_DONE = B_STE + 16;
constexpr uint32_t B_LN = B_DONE + 8;
constexpr uint32_t RDY_OFF = B_LN + 24;
constexpr uint32_t ITEM_OFF = RDY_OFF + 512;
constexpr uint32_t MISC_OFF = ITEM_OFF + 256;
constexpr uint32_t SMEM_BYTES = MISC_OFF + 64 + 1024;

enum { TM_XN = 0, TM_CKV, TM_H, TM_CTX, TM_WUK, TM_WUV, TM_WG, TM_WU, TM_WD, TM_WO, TM_WQ, TM_KVL, TM_XQ, TM_XQ1, TM_GL,
       TM_KVS, TM_HS, TM_GS, TM_OUTS, TM_CTXS, TM_COUNT };

enum { IT_KV = 0, IT_GU = 1, IT_DN = 2, IT_OP = 3, IT_AT = 4, IT_END = 7 };
__host__ __device__ inline uint32_t mk_item(int type, int j, int idx, int k0, int nk, int lead) {
  return (uint32_t)type | (j << 3) | (idx << 6) | (k0 << 11) | (nk << 17) | (lead << 24);
}
constexpr int MAX_ITEMS = 1024;
constexpr int MAX_CL = 72;

struct Params {
  const bf16* x;
  bf16* out;
  bf16* xn;
  unsigned* flags;
  uint32_t ends[8];
  uint16_t off[MAX_CL + 8];
  uint32_t items[MAX_ITEMS];
  CUtensorMap tm[TM_COUNT];
};

constexpr int F_LN = 0;
constexpr int F_KV = 32;
constexpr int F_H = F_KV + 512;
constexpr int F_CTX = F_H + 512;
constexpr int F_G = F_CTX + 512;
constexpr int F_START = F_G + 32;
constexpr int F_EPOCH = F_START + 32;
constexpr int F_DYN = F_EPOCH + 32;
constexpr int F_COUNT = F_DYN + 128;

__device__ __align__(1024) bf16 g_xn[SEQ * DM];
__device__ __align__(1024) bf16 g_kv[SEQ * 8192];
__device__ __align__(1024) bf16 g_h[SEQ * DFF];
__device__ __align__(1024) bf16 g_ctx[SEQ * 4096];
__device__ __align__(1024) bf16 g_gate[SEQ * DM];
__device__ unsigned g_flags[F_COUNT];
#define ST(id)
#define T5(n, id)
#define T4(c)
#define PZ 0
#define T6(c, id) do { if ((PZ >> (id)) & 1) asm volatile("" : "+r"((c).ph)); } while (0)
#define TX(c, id)
#define EV(c, id)
#define PEV(id)

__device__ __forceinline__ uint32_t smem_u32(const void* p) { return (uint32_t)__cvta_generic_to_shared(p); }
__device__ __forceinline__ void mbar_init(uint32_t bar, int cnt) {
  asm volatile("mbarrier.init.shared::cta.b64 [%0], %1;" ::"r"(bar), "r"(cnt));
}
__device__ __forceinline__ void mbar_expect_tx(uint32_t bar, uint32_t bytes) {
  asm volatile("mbarrier.arrive.expect_tx.shared::cta.b64 _, [%0], %1;" ::"r"(bar), "r"(bytes) : "memory");
}
__device__ __forceinline__ void mbar_arrive(uint32_t bar) {
  asm volatile("mbarrier.arrive.shared::cta.b64 _, [%0];" ::"r"(bar) : "memory");
}
__device__ __forceinline__ void mbar_arrive_cta(uint32_t bar, uint32_t cta) {
  asm volatile("{\n.reg .b32 ra;\nmapa.shared::cluster.u32 ra, %0, %1;\nmbarrier.arrive.shared::cluster.b64 _, [ra];\n}"
               ::"r"(bar), "r"(cta) : "memory");
}
__device__ __forceinline__ void mbar_arrive_cta4(uint32_t bar, uint32_t cta) {
  asm volatile("{\n.reg .b32 ra;\nmapa.shared::cluster.u32 ra, %0, %1;\nmbarrier.arrive.shared::cluster.b64 _, [ra], 4;\n}"
               ::"r"(bar), "r"(cta) : "memory");
}
__device__ __forceinline__ bool mbar_try(uint32_t bar, uint32_t parity) {
  uint32_t ok;
  asm volatile("{\n.reg .pred p;\nmbarrier.try_wait.parity.shared::cta.b64 p, [%1], %2;\nselp.u32 %0, 1, 0, p;\n}"
               : "=r"(ok) : "r"(bar), "r"(parity) : "memory");
  return ok != 0;
}
#define HINT 2000
#define HINTP
__device__ __forceinline__ bool mbar_try_long(uint32_t bar, uint32_t parity) {
  uint32_t ok;
  asm volatile("{\n.reg .pred p;\nmbarrier.try_wait.parity.shared::cta.b64 p, [%1], %2, %3;\nselp.u32 %0, 1, 0, p;\n}"
               : "=r"(ok) : "r"(bar), "r"(parity), "r"(HINT) : "memory");
  return ok != 0;
}
__device__ __forceinline__ bool mbar_test(uint32_t bar, uint32_t parity) {
  uint32_t ok;
  asm volatile("{\n.reg .pred p;\nmbarrier.test_wait.parity.shared::cta.b64 p, [%1], %2;\nselp.u32 %0, 1, 0, p;\n}"
               : "=r"(ok) : "r"(bar), "r"(parity) : "memory");
  return ok != 0;
}
__device__ __forceinline__ uint32_t clk32() {
  uint32_t t;
  asm volatile("mov.u32 %0, %%clock;" : "=r"(t));
  return t;
}
__device__ __forceinline__ void spin_guard(uint32_t t0) {
  asm volatile("{\n.reg .pred p;\n.reg .s32 d;\nmov.u32 d, %%clock;\nsub.s32 d, d, %0;\nsetp.lt.s32 p, d, 0;\n@p st.global.u32 [%1], %0;\n}"
               ::"r"(t0), "l"(0ull) : "memory");
}
__device__ __forceinline__ void mbar_wait(uint32_t bar, uint32_t parity) {
  if (mbar_try(bar, parity)) return;
  const uint32_t t0 = clk32();
  while (!mbar_try(bar, parity)) spin_guard(t0);
}
#define NAP 100
__device__ __forceinline__ void mbar_wait_st(uint32_t bar, uint32_t parity) {
  if (HINT) {
    const uint32_t t0 = clk32();
    while (!mbar_try_long(bar, parity)) spin_guard(t0);
  } else {
    mbar_wait(bar, parity);
  }
}
__device__ __forceinline__ void mbar_wait_nap(uint32_t bar, uint32_t parity) {
  if (mbar_try(bar, parity)) return;
  const uint32_t t0 = clk32();
  while (!mbar_try_long(bar, parity)) spin_guard(t0);
  return;
  do {
    if (NAP) __nanosleep(NAP);
    spin_guard(t0);
  } while (!mbar_try(bar, parity));
}
__device__ __forceinline__ bool elect_one() {
  uint32_t p;
  asm volatile("{\n.reg .pred p;\nelect.sync _|p, 0xffffffff;\nselp.u32 %0, 1, 0, p;\n}" : "=r"(p));
  return p != 0;
}
__device__ __forceinline__ void tma_load_3d(uint32_t dst, const CUtensorMap* m, uint32_t bar, int c0, int c1, int c2) {
  asm volatile("cp.async.bulk.tensor.3d.shared::cluster.global.mbarrier::complete_tx::bytes [%0], [%1, {%3, %4, %5}], [%2];"
               ::"r"(dst), "l"(m), "r"(bar), "r"(c0), "r"(c1), "r"(c2) : "memory");
}
__device__ __forceinline__ void tma_load_2d(uint32_t dst, const CUtensorMap* m, uint32_t bar, int c0, int c1) {
  asm volatile("cp.async.bulk.tensor.2d.shared::cluster.global.mbarrier::complete_tx::bytes [%0], [%1, {%3, %4}], [%2];"
               ::"r"(dst), "l"(m), "r"(bar), "r"(c0), "r"(c1) : "memory");
}
__device__ __forceinline__ void tma_load_2d_mc(uint32_t dst, const CUtensorMap* m, uint32_t bar, int c0, int c1, uint32_t last) {
  asm volatile("{\n.reg .b64 pol;\nmov.b64 pol, {0, %6};\n"
               "cp.async.bulk.tensor.2d.shared::cluster.global.mbarrier::complete_tx::bytes.multicast::cluster.L2::cache_hint [%0], [%1, {%3, %4}], [%2], %5, pol;\n}"
               ::"r"(dst), "l"(m), "r"(bar), "r"(c0), "r"(c1), "h"((uint16_t)3), "r"(last ? 0x12F00000u : 0x10000000u) : "memory");
}
__device__ __forceinline__ void tma_load_3d_mc(uint32_t dst, const CUtensorMap* m, uint32_t bar, int c0, int c1, int c2, uint32_t last) {
  asm volatile("{\n.reg .b64 pol;\nmov.b64 pol, {0, %7};\n"
               "cp.async.bulk.tensor.3d.shared::cluster.global.mbarrier::complete_tx::bytes.multicast::cluster.L2::cache_hint [%0], [%1, {%3, %4, %5}], [%2], %6, pol;\n}"
               ::"r"(dst), "l"(m), "r"(bar), "r"(c0), "r"(c1), "r"(c2), "h"((uint16_t)3), "r"(last ? 0x12F00000u : 0x10000000u) : "memory");
}
__device__ __forceinline__ void tma_store_2d(const CUtensorMap* m, uint32_t src, int c0, int c1) {
  asm volatile("cp.async.bulk.tensor.2d.global.shared::cta.bulk_group [%0, {%2, %3}], [%1];"
               ::"l"(m), "r"(src), "r"(c0), "r"(c1) : "memory");
}
__device__ __forceinline__ void tma_reduce_2d(const CUtensorMap* m, uint32_t src, int c0, int c1) {
  asm volatile("cp.reduce.async.bulk.tensor.2d.global.shared::cta.add.bulk_group [%0, {%2, %3}], [%1];"
               ::"l"(m), "r"(src), "r"(c0), "r"(c1) : "memory");
}
__device__ __forceinline__ unsigned ld_acquire(const unsigned* p) {
  unsigned v;
  asm volatile("ld.acquire.gpu.global.u32 %0, [%1];" : "=r"(v) : "l"(p) : "memory");
  return v;
}
__device__ __forceinline__ unsigned ld_relaxed(const unsigned* p) {
  unsigned v;
  asm volatile("ld.relaxed.gpu.global.u32 %0, [%1];" : "=r"(v) : "l"(p) : "memory");
  return v;
}
#define FASTW 1
#define FASTR 1
#define DEP_NAP 100
__device__ __forceinline__ void red_release(unsigned* p) {
  asm volatile("red.release.gpu.global.add.u32 [%0], 1;" ::"l"(p) : "memory");
}
__device__ __forceinline__ void red_relaxed(unsigned* p) {
  asm volatile("red.relaxed.gpu.global.add.u32 [%0], 1;" ::"l"(p) : "memory");
}
__device__ __forceinline__ void wait_flag(const unsigned* p, unsigned target) {
  const uint32_t t0 = clk32();
  while ((int)(ld_acquire(p) - target) < 0) {
    __nanosleep(40);
    spin_guard(t0);
  }
}
__device__ __forceinline__ uint64_t mkdesc(uint32_t addr, uint32_t lbo, uint32_t sbo) {
  return (uint64_t)((addr & 0x3FFFF) >> 4) | ((uint64_t)(lbo >> 4) << 16) | ((uint64_t)(sbo >> 4) << 32) | (1ull << 62);
}
#define WG_FENCE() asm volatile("wgmma.fence.sync.aligned;" ::: "memory")
#define WG_COMMIT() asm volatile("wgmma.commit_group.sync.aligned;" ::: "memory")
#define WG_WAIT(n) asm volatile("wgmma.wait_group.sync.aligned %0;" ::"n"(n) : "memory")
template <int N> __device__ __forceinline__ void fence_regs(float (&r)[N]) {
#pragma unroll
  for (int i = 0; i < N; i++) asm volatile("" : "+f"(r[i])::"memory");
}
template <int N> __device__ __forceinline__ void fence_regs(uint32_t (&r)[N]) {
#pragma unroll
  for (int i = 0; i < N; i++) asm volatile("" : "+r"(r[i])::"memory");
}
__device__ __forceinline__ uint32_t pack_bf16(float lo, float hi) {
  uint32_t r;
  asm("cvt.rn.bf16x2.f32 %0, %1, %2;" : "=r"(r) : "f"(hi), "f"(lo));
  return r;
}
__device__ __forceinline__ float round_bf16(float v) { return __bfloat162float(__float2bfloat16_rn(v)); }
__device__ __forceinline__ float ex2(float x) {
  float y;
  asm("ex2.approx.ftz.f32 %0, %1;" : "=f"(y) : "f"(x));
  return y;
}
__device__ __forceinline__ void stsm_x4(uint32_t addr, uint32_t a, uint32_t b, uint32_t c, uint32_t d) {
  asm volatile("stmatrix.sync.aligned.m8n8.x4.shared.b16 [%0], {%1, %2, %3, %4};" ::"r"(addr), "r"(a), "r"(b), "r"(c), "r"(d) : "memory");
}
__device__ __forceinline__ void ldsm_x4(uint32_t addr, uint32_t* r) {
  asm volatile("ldmatrix.sync.aligned.m8n8.x4.shared.b16 {%0, %1, %2, %3}, [%4];"
               : "=r"(r[0]), "=r"(r[1]), "=r"(r[2]), "=r"(r[3]) : "r"(addr) : "memory");
}
__device__ __forceinline__ float tanh_f(float x) {
  float y;
  asm("tanh.approx.f32 %0, %1;" : "=f"(y) : "f"(x));
  return y;
}
__device__ __forceinline__ float bf_lo(uint32_t v) { return __uint_as_float(v << 16); }
__device__ __forceinline__ float bf_hi(uint32_t v) { return __uint_as_float(v & 0xffff0000u); }
__device__ __forceinline__ void bar_sync(int id, int n) { asm volatile("bar.sync %0, %1;" ::"r"(id), "r"(n) : "memory"); }
__device__ __forceinline__ void bar_arrive(int id, int n) { asm volatile("bar.arrive %0, %1;" ::"r"(id), "r"(n) : "memory"); }
__device__ __forceinline__ void cluster_sync() {
  asm volatile("barrier.cluster.arrive.aligned;\nbarrier.cluster.wait.aligned;" ::: "memory");
}

struct Ring {
  uint32_t gs, as;
  uint32_t gph, aph;
  uint32_t mode;
  __device__ __forceinline__ void to_g() {
    if (mode != 0) { mode = 0; gs = (0x032210u >> (as * 4)) & 3; }
  }
  __device__ __forceinline__ void to_a() {
    if (mode != 1) { mode = 1; as = (0x5320u >> (gs * 4)) & 7; }
  }
};

#define PEEK 1
#define FENCE_MODE 2
struct Cons {
  uint32_t sb;
  uint32_t lane, wi, w;
  uint32_t s;
  uint32_t ph;
  uint32_t ia;
  uint32_t pn, pt;
  bool pre;
  __device__ __forceinline__ uint32_t item() {
    uint32_t v;
    asm volatile("ld.shared.u32 %0, [%1];" : "=r"(v) : "r"(ia));
    return v;
  }
  __device__ __forceinline__ uint32_t peek() {
    uint32_t v;
    asm volatile("ld.shared.u32 %0, [%1 + 4];" : "=r"(v) : "r"(ia));
    s = (((v & 7) == IT_AT ? 0x9876549764ull : 0x0322103210ull) >> (s * 4)) & 15;
    asm volatile("" : "+r"(v));
    return v;
  }
  __device__ __forceinline__ bool probe() {
    const uint32_t s1 = (0x4987650321ull >> (s * 4)) & 15;
    return mbar_test(sb + B_FULLG + s * 8, (ph >> s) & 1) & mbar_test(sb + B_FULLG + s1 * 8, (ph >> s1) & 1);
  }
  __device__ __forceinline__ void release(uint32_t slot) {
    asm volatile("{\n.reg .pred p;\n.reg .b32 ra;\nsetp.lt.u32 p, %1, 2;\nand.b32 ra, %1, 1;\nmapa.shared::cluster.u32 ra, %0, ra;\n@p mbarrier.arrive.shared::cluster.b64 _, [ra];\n}"
                 ::"r"(sb + B_EMPTYG + slot * 8), "r"(lane) : "memory");
  }
  __device__ __forceinline__ void stage_wait() { mbar_wait(sb + B_STE + w * 8, (ph >> 10) & 1); }
  __device__ __forceinline__ bool full_g(uint32_t s) { return __all_sync(0xffffffffu, mbar_test(sb + B_FULLG + s * 8, (ph >> s) & 1)); }
  __device__ __forceinline__ bool stage_free() { return __all_sync(0xffffffffu, mbar_test(sb + B_STE + w * 8, (ph >> 10) & 1)); }
  __device__ __forceinline__ uint32_t box_addr(uint32_t base) {
    return base + (wi * 16 + ((lane >> 3) & 1) * 8 + (lane & 7)) * 128 + (((lane >> 4) ^ (lane & 7)) << 4);
  }
  __device__ __forceinline__ void put_box(uint32_t base, const uint32_t* p, uint32_t off = 0) {
#pragma unroll
    for (int kk = 0; kk < 4; kk++) stsm_x4((box_addr(base) ^ (kk * 32)) + off, p[4 * kk], p[4 * kk + 1], p[4 * kk + 2], p[4 * kk + 3]);
  }
  __device__ __forceinline__ void get_box(uint32_t base, uint32_t* p, uint32_t off) {
#pragma unroll
    for (int kk = 0; kk < 4; kk++) ldsm_x4((box_addr(base) ^ (kk * 32)) + off, &p[4 * kk]);
  }
  __device__ __forceinline__ void stage_done() {
    __syncwarp();
    if (lane == 0) mbar_arrive(sb + B_STF + w * 8);
    ph ^= 1024;
  }
};

#define GU2 1
__device__ __forceinline__ float gelu_mul(float g, float u) {
  const float z = g * fmaf(g * g, 0.044715f * 0.7978845608028654f, 0.7978845608028654f);
  const float hu = 0.5f * g * u;
  return fmaf(hu, tanh_f(z), hu);
}
__device__ __forceinline__ float silu_f(float d) {
  const float hd = 0.5f * d;
  return fmaf(hd, tanh_f(hd), hd);
}
__device__ __forceinline__ uint32_t mul_bf16(uint32_t a, uint32_t b) {
  uint32_t r;
  asm("mul.rn.bf16x2 %0, %1, %2;" : "=r"(r) : "r"(a), "r"(b));
  return r;
}
__device__ __forceinline__ float gelu2(float g) {
  return fmaf(g, tanh_f(g * fmaf(g * g, 0.044715f * 0.7978845608028654f, 0.7978845608028654f)), g);
}
__device__ __forceinline__ float silu_h(float hd) { return fmaf(hd, tanh_f(hd), hd); }

template <bool V> struct Flag { static constexpr bool value = V; };
__device__ __forceinline__ void flush_piece(Cons& c, uint32_t (&pd)[64]) {
  const uint32_t a = c.box_addr(c.sb + STG_OFF + c.w * 16384);
  if (!(c.pt & 3)) {
    auto put = [&](const uint32_t* p) {
#pragma unroll
      for (int q = 0; q < 8; q++) stsm_x4((a ^ ((q & 1) * 32 + (q >> 2) * 64)) + ((q >> 1) & 1) * 8192, p[4 * q], p[4 * q + 1], p[4 * q + 2], p[4 * q + 3]);
    };
    if (c.pn == 4) put(pd);
    else put(pd + 32);
    c.stage_done();
    c.pn -= 2;
  } else {
    auto pull = [&](int o) {
#pragma unroll
      for (int i = 0; i < 16; i++) asm volatile("mov.b32 %0, %1;" : "=r"(pd[i]) : "r"(pd[o + i]));
    };
    if (c.pn == 3) pull(16);
    else if (c.pn == 2) pull(32);
    else if (c.pn == 1) pull(48);
    uint32_t h = a ^ ((c.pn & 1) * 64);
    if (c.pt == IT_GU) {
#pragma unroll
      for (int i = 0; i < 8; i++)
        if (GU2) pd[i] = mul_bf16(pack_bf16(gelu2(bf_lo(pd[i])), gelu2(bf_hi(pd[i]))), pd[8 + i]);
        else pd[i] = pack_bf16(gelu_mul(bf_lo(pd[i]), bf_lo(pd[8 + i])), gelu_mul(bf_hi(pd[i]), bf_hi(pd[8 + i])));
      if (c.pn <= 2) h += 8192;
    } else {
#pragma unroll
      for (int i = 0; i < 16; i++) {
        if (GU2) {
          const uint32_t hd = mul_bf16(pd[i], 0x3e803e80u);
          pd[i] = pack_bf16(silu_h(bf_lo(hd)), silu_h(bf_hi(hd)));
        } else {
          pd[i] = pack_bf16(silu_f(bf_lo(pd[i])), silu_f(bf_hi(pd[i])));
        }
      }
      stsm_x4(h + 8192, pd[8], pd[9], pd[10], pd[11]);
      stsm_x4((h ^ 32) + 8192, pd[12], pd[13], pd[14], pd[15]);
    }
    stsm_x4(h, pd[0], pd[1], pd[2], pd[3]);
    stsm_x4(h ^ 32, pd[4], pd[5], pd[6], pd[7]);
    if ((c.pn & (c.pt == IT_GU ? 3 : 1)) == 1) c.stage_done();
    c.pn--;
  }
  EV(c, 24);
}
template <class F>
__device__ __forceinline__ void flush_some(Cons& c, uint32_t (&pd)[64], F go, bool lazy = false) {
  if (c.pn && !(lazy && go())) {
    const uint32_t t0 = clk32();
    do {
      if ((c.pn & 1) || c.stage_free()) flush_piece(c, pd);
      else spin_guard(t0);
    } while (c.pn && !go());
  }
}

#define STAG 4
#define SROWS 32
#define SOUT 0
#define SGAP 0
#define OPE 1
#define SGD 3
#define EF 1
#define TMP 2
#define NSP 1
#define PV 198
#define ORD 0
#define DLY 0
#define DYN0 3
#define WRED 1
#define EG2 1
#define PFQ 0
#define LND 0
#define LATE 2
#define SOUT0 3
#define NEED1 1
__device__ __forceinline__ uint32_t gemm_item(Cons& c, uint32_t item, uint32_t rank, const CUtensorMap* to, uint32_t (&pd)[64]) {
  float acc[128];
  uint32_t prev = 0;
  EV(c, 20);
  auto kstep = [&](auto first) {
    const uint32_t s = c.s;
    if (!first.value || !c.pre) mbar_wait(c.sb + B_FULLG + s * 8, (c.ph >> s) & 1);
    EV(c, 21);
    c.ph ^= 1u << s;
    c.s = (s + 1) & 3;
    const uint32_t base = c.sb + s * 49152;
    const uint64_t da = mkdesc(base + c.w * 8192, 16, 1024);
    const uint64_t db = mkdesc(base + 16384, 8192, 1024);
    WG_FENCE();
#pragma unroll
    for (int kk = 0; kk < 4; kk++) wgmma_ss_n256<1>(acc, da + kk * 2, db + kk * 128, kk || !first.value);
    WG_COMMIT();
    return s;
  };
  T6(c, 0);
  prev = kstep(Flag<true>());
  T6(c, 1);
  if (EF && c.pn && (EF == 1 ? c.pt == IT_AT : !(c.pt & 3) && c.stage_free())) {
    const uint32_t a = c.box_addr(c.sb + STG_OFF + c.w * 16384);
    auto put = [&](const uint32_t* p) {
#pragma unroll
      for (int q = 0; q < 8; q++) stsm_x4((a ^ ((q & 1) * 32 + (q >> 2) * 64)) + ((q >> 1) & 1) * 8192, p[4 * q], p[4 * q + 1], p[4 * q + 2], p[4 * q + 3]);
    };
    if (EF == 2 && c.pn == 4) put(pd);
    else put(pd + 32);
    c.stage_done();
    c.pn -= 2;
  }
  const uint32_t stg = c.sb + STG_OFF + c.w * 16384;
  uint32_t gq = (item & 7) == IT_OP;
  auto gate = [&](uint32_t* g) {
    c.get_box(stg, g, 0);
    c.get_box(stg, g + 16, 8192);
  };
  auto gate1 = [&] {
    gate(pd);
    uint32_t t = 0;
#pragma unroll
    for (int i = 0; i < 32; i += 4) t |= pd[i];
    if (((t & blockIdx.y) | c.lane) == 0) mbar_arrive(c.sb + B_STF + c.w * 8);
    c.ph ^= 1024;
  };
  int left = ((item >> 17) & 127) - 2;
  const int stop = gq * 3;
  auto more = [&] {
    mbar_wait(c.sb + B_FULLG + c.s * 8, (c.ph >> c.s) & 1);
    uint32_t v;
    asm volatile("ld.shared.u32 %0, [%1];" : "=r"(v) : "r"(c.sb + MISC_OFF + 32 + c.s * 8) : "memory");
    return v != 0;
  };
#pragma unroll 1
  do {
    const uint32_t s = kstep(Flag<false>());
    WG_WAIT(1);
    c.release(prev);
    if (c.pn | gq) {
      if (c.pn) flush_some(c, pd, [&] { return left != stop && c.full_g(c.s); }, (LATE && c.pt + left > 8 + LATE && c.pt == 8) || (STAG && c.pt == IT_GU && ((left ^ c.w) & 1) && c.pn < STAG));
      else if (c.stage_free()) { gate1(); gq = 0; }
    }
    prev = s;
  } while (--left >= stop || (stop && more()));
  T6(c, 12);
  item = c.item();
  const int type = item & 7;
  if (type != IT_OP) {
    item = c.peek();
    WG_WAIT(0);
    fence_regs(acc);
    T6(c, 13);
    c.release(prev);
    EV(c, 22);
    const bool ok = c.probe();
#pragma unroll
    for (int i = 0; i < 64; i++) {
      const int e = (i >> 4) * 16 + ((i >> 3) & 1) * 64 + (i & 7) * 2;
      pd[i] = pack_bf16(acc[e], acc[e + 1]);
    }
    fence_regs(pd);
    c.pre = __all_sync(0xffffffffu, ok);
    c.pn = 4;
    c.pt = type | (LATE ? (item >> 26) & 8 : 0);
  } else {
    float (&lo)[64] = *(float (*)[64])acc;
    float (&hi)[64] = *(float (*)[64])(acc + 64);
    auto gate2 = [&] {
      if (gq) {
        c.stage_wait();
        gate1();
      }
      c.stage_wait();
      gate(pd + 32);
      fence_regs(pd);
    };
    auto part = [&](float (&h)[64], uint32_t s, uint32_t o) {
      const uint32_t base = c.sb + (s & 3) * 49152;
      const uint64_t da = mkdesc(base + c.w * 8192, 16, 1024), db = mkdesc(base + o, 8192, 1024);
      WG_FENCE();
#pragma unroll
      for (int kk = 0; kk < 4; kk++) wgmma_ss_n128<1>(h, da + kk * 2, db + kk * 128, 1);
      WG_COMMIT();
    };
    const uint32_t lw = (c.w ^ (item >> 24)) & 1;
    if (lw) {
      WG_WAIT(0);
      c.release(prev);
    }
    const bool g2 = lw || (EG2 && !gq && c.stage_free());
    if (g2) gate2();
    TX(c, 0);
    if (lw) bar_sync(5, 256);
    TX(c, 1);
    const uint32_t gs = prev;
#pragma unroll 1
    for (int q = 0; q < 3; q++) {
      mbar_wait(c.sb + B_FULLG + c.s * 8, (c.ph >> c.s) & 1);
      c.ph ^= 1u << c.s;
      part(hi, c.s, 32768);
      c.s = (c.s + 1) & 3;
      if (!(q | lw)) {
        WG_WAIT(1);
        c.release(prev);
      }
    }
    TX(c, 2);
    part(lo, gs + 1, 16384);
    part(lo, gs + 2, 16384);
    TX(c, 3);
    if (!g2) gate2();
    c.s = (gs + 1) & 3;
    const int col = ((item >> 6) & 31) * 256 + (item >> 28) * 128, row = (((item >> 3) & 7) * 2 + rank) * 128 + c.w * 64 + c.wi * 16;
    item = c.peek();
    TX(c, 4);
    WG_WAIT(2);
    fence_regs(hi);
    TX(c, 5);
#pragma unroll
    for (int b = 3; b >= 0; b--) {
      if (b == 2) {
        part(lo, gs + 3, 16384);
        if (!lw) bar_arrive(5, 256);
      }
      if (b == 1) {
        TX(c, 6);
        WG_WAIT(0);
        fence_regs(lo);
        TX(c, 7);
        T6(c, 13);
        c.release((gs + 1) & 3);
        c.release((gs + 2) & 3);
        c.release((gs + 3) & 3);
      }
#pragma unroll
      for (int i = b * 16; i < b * 16 + 16; i++) pd[i] = mul_bf16(pack_bf16(acc[2 * i], acc[2 * i + 1]), pd[i]);
      if (b == 1) {
        mbar_wait(c.sb + B_FULLG + gs * 8, (c.ph >> gs) & 1);
        c.ph ^= 1u << gs;
      }
      c.put_box(b < 2 ? c.sb + gs * 49152 + c.w * 8192 : stg, pd + b * 16, b < 2 ? b * 16384 : (b - 2) * 8192);
      asm volatile("fence.proxy.async.shared::cta;" ::: "memory");
      __syncwarp();
      if (c.lane == 0)
        tma_reduce_2d(to, (b < 2 ? c.sb + gs * 49152 + c.w * 8192 + b * 16384 : stg + (b - 2) * 8192) + c.wi * 2048, col ^ (b * 64), row);
      if (b == 3) TX(c, 9);
    }
    TX(c, 8);
    if (c.lane == 0) asm volatile("cp.async.bulk.commit_group;\ncp.async.bulk.wait_group.read 0;" ::: "memory");
    __syncwarp();
    TX(c, 12);
    c.release(gs);
    c.stage_done();
    c.pre = __all_sync(0xffffffffu, c.probe());
  }
  EV(c, 23);
  T6(c, 14);
  return item;
}

struct Slot { uint32_t s, ph; };
__device__ __forceinline__ Slot take_a(Cons& c) {
  Slot t;
  t.s = c.s;
  t.ph = (c.ph >> t.s) & 1;
  c.ph ^= 1u << t.s;
  c.s = (t.s == 9) ? 4 : t.s + 1;
  return t;
}
constexpr uint32_t A0 = 4 * 32768;

__device__ __forceinline__ void qk_issue(float (&S)[64], uint32_t qbase, uint32_t kbase) {
  uint64_t da = mkdesc(qbase, 16, 1024);
  uint64_t db = mkdesc(kbase, 16, 1024);
#pragma unroll
  for (int kk = 0; kk < 8; kk++)
    wgmma_ss_n128<0>(S, da + (kk >> 2) * 512 + (kk & 3) * 2, db + (kk >> 2) * 1024 + (kk & 3) * 2, kk != 0);
}
__device__ __forceinline__ void qk_issue_r(float (&S)[64], const uint32_t (&Q)[32], uint32_t kbase) {
  uint64_t db = mkdesc(kbase, 16, 1024);
#pragma unroll
  for (int kk = 0; kk < 8; kk++)
    wgmma_rs_n128<0>(S, Q[4 * kk], Q[4 * kk + 1], Q[4 * kk + 2], Q[4 * kk + 3], db + (kk >> 2) * 1024 + (kk & 3) * 2, kk != 0);
}
__device__ __forceinline__ void pv_issue(float (&O)[64], const uint32_t (&P)[32], uint32_t vbase) {
  uint64_t db = mkdesc(vbase, 16384, 1024);
#pragma unroll
  for (int kk = 0; kk < 8; kk++)
    wgmma_rs_n128<1>(O, P[4 * kk], P[4 * kk + 1], P[4 * kk + 2], P[4 * kk + 3], db + kk * 128, 1);
}

#define DREF 1
#define QL 9
#define DF 0
#define KL 0
#define QMH 0x6a
#define QSH QMH
#define QMK 0x42
#define QSK 0x88
#define QMA 0x02
#define QSA 0x20
constexpr float CS = 0.08838834764831845f * 1.4426950408889634f;
#define LAZYS 1.152921504606846976e18f
constexpr float LAZY_SUM = LAZYS;

struct Soft {
  float n0, n1, l0, l1;
  __device__ __forceinline__ void refresh(const float (&S)[64], float& sc0, float& sc1) {
    float x0 = fmaxf(S[0], S[1]), x1 = fmaxf(S[2], S[3]);
#pragma unroll
    for (int b = 1; b < 16; b++) {
      x0 = fmaxf(x0, fmaxf(S[4 * b], S[4 * b + 1]));
      x1 = fmaxf(x1, fmaxf(S[4 * b + 2], S[4 * b + 3]));
    }
    x0 = fmaxf(x0, __shfl_xor_sync(0xffffffffu, x0, 1));
    x1 = fmaxf(x1, __shfl_xor_sync(0xffffffffu, x1, 1));
    x0 = fmaxf(x0, __shfl_xor_sync(0xffffffffu, x0, 2));
    x1 = fmaxf(x1, __shfl_xor_sync(0xffffffffu, x1, 2));
    x0 = fminf(n0, -x0 * CS);
    x1 = fminf(n1, -x1 * CS);
    sc0 = ex2(x0 - n0);
    sc1 = ex2(x1 - n1);
    n0 = x0; n1 = x1;
  }
  template <int N>
  __device__ __forceinline__ void numer(const float (&S)[N], uint32_t* P, float& b0, float& b1, bool add) {
#pragma unroll
    for (int b = 0; b < N / 4; b++) {
      const float e0 = ex2(fmaf(S[4 * b], CS, n0)), e1 = ex2(fmaf(S[4 * b + 1], CS, n0));
      const float e2 = ex2(fmaf(S[4 * b + 2], CS, n1)), e3 = ex2(fmaf(S[4 * b + 3], CS, n1));
      if (b == 0 && !add) { b0 = e0 + e1; b1 = e2 + e3; } else { b0 += e0 + e1; b1 += e2 + e3; }
      P[2 * b] = pack_bf16(e0, e1);
      P[2 * b + 1] = pack_bf16(e2, e3);
    }
  }
};

#define TI(id)
template <bool ODD>
__device__ __forceinline__ void attn_step(Cons& c, float (&S)[64], float (&O)[64], uint32_t (&Pc)[32], uint32_t (&Pn)[32],
                                          Soft& f, Slot& tk, Slot& tv, bool more, uint32_t qbase, bool later) {
  const uint32_t ek = tk.s, ev = tv.s;
  tk = take_a(c);
  tv = tk;
  if (more) tv = take_a(c);
  if (!ODD || later) {
    bar_sync(3 + c.w, 256);
    if (!ODD && !later) T6(c, 11);
    TI(4);
    fence_regs(Pc);
    fence_regs(O);
    WG_FENCE();
    qk_issue(S, qbase, c.sb - A0 + ek * 32768);
    WG_COMMIT();
    pv_issue(O, Pc, c.sb - A0 + ev * 32768);
    WG_COMMIT();
    bar_arrive(4 - c.w, 256);
    TI(5);
    WG_WAIT(1);
  }
  fence_regs(S);
  TI(6);
  c.release(ek);
  float b0, b1;
  f.numer(S, Pn, b0, b1, false);
  const bool ok = mbar_test(c.sb + B_FULLG + tk.s * 8, tk.ph) & mbar_test(c.sb + B_FULLG + tv.s * 8, tv.ph);
  if (__any_sync(0xffffffffu, fmaxf(b0, b1) > LAZY_SUM)) {
    float sc0, sc1;
    f.refresh(S, sc0, sc1);
    f.l0 *= sc0; f.l1 *= sc1;
    WG_WAIT(0);
    fence_regs(O);
#pragma unroll
    for (int b = 0; b < 16; b++) { O[4 * b] *= sc0; O[4 * b + 1] *= sc0; O[4 * b + 2] *= sc1; O[4 * b + 3] *= sc1; }
    f.numer(S, Pn, b0, b1, false);
  }
  f.l0 += b0; f.l1 += b1;
  TI(7);
  WG_WAIT(0);
  TI(8);
  c.release(ev);
  if (ODD && !later) T6(c, 10);
  if (!ok) {
    mbar_wait(c.sb + B_FULLG + tk.s * 8, tk.ph);
    mbar_wait(c.sb + B_FULLG + tv.s * 8, tv.ph);
  }
}

__device__ __forceinline__ uint32_t attn_item(Cons& c, uint32_t item, uint32_t rank, uint32_t (&pd)[64]) {
  float S[64];
  uint32_t P[32], P2[32];
  const uint32_t qbase = c.sb + STG_OFF + c.w * 16384;
  bool ok = c.pre;
  auto chunk = [&](auto first) {
    const Slot tx = take_a(c);
    if (!ok) mbar_wait(c.sb + B_FULLG + tx.s * 8, tx.ph);
    const uint64_t da = mkdesc(c.sb - A0 + tx.s * 32768 + ((((item >> 24) ^ c.w) & 1) ? 0 : 8192), 16, 1024);
    const uint64_t db = mkdesc(c.sb - A0 + tx.s * 32768 + 16384, 8192, 1024);
    WG_FENCE();
#pragma unroll
    for (int kk = 0; kk < 4; kk++) wgmma_ss_n128<1>(S, da + kk * 2, db + kk * 128, kk || !first.value);
    WG_COMMIT();
    return tx.s;
  };
  T6(c, 0);
  uint32_t px = chunk(Flag<true>());
  uint32_t sx = chunk(Flag<false>());
#pragma unroll 1
  for (;;) {
    const int j = (item >> 3) & 7;
    const bool lng = (((item >> 24) & 1) == c.w);
    const uint32_t odd = lng ? (rank ^ 1) : rank;
    const int nblk = 2 * j + (lng ? 2 : 1);
    Soft f;
    Slot tk, tv;
    float O[64];
    T6(c, 1);
    uint32_t fm = (c.pt & 3) ? (lng ? QMH : QSH) : c.pn > 2 ? (lng ? QMK : QSK) : (lng ? QMA : QSA);
#pragma unroll 1
    for (fm |= 0x8000;;) {
      ok = mbar_test(c.sb + B_FULLG + c.s * 8, (c.ph >> c.s) & 1);
      fm >>= 1;
      if ((fm & 255) == 1) T6(c, 2);
      if (fm & 1) flush_some(c, pd, [&] { return (fm & 255) != 1; });
      if ((fm & 255) == 1) T6(c, 3);
      if (fm & 256) break;
      WG_WAIT(1);
      c.release(px);
      px = sx;
      sx = chunk(Flag<false>());
    }
    {
      float D[32], F[32];
      {
        const float r0 = (float)(int)(c.wi * 16 + (c.lane >> 2) - (c.lane & 3) * 2);
#pragma unroll
        for (int i = 0; i < 32; i++) F[i] = 0.f;
        D[2] = 0.f; D[3] = 0.f;
#pragma unroll
        for (int i = 0; i < 16; i++) {
          float m;
          asm("sub.sat.f32 %0, %1, %2;" : "=f"(m) : "f"((float)((i >> 1) * 8 + (i & 1))), "f"(r0));
          D[(i >> 1) * 4 + (i & 1)] = m * -3e38f;
          if (i < 14) asm("mul.f32 %0, %1, %2;" : "=f"(D[(i >> 1) * 4 + (i & 1) + 6]) : "f"(m), "f"(-3.0001e38f));
        }
        fence_regs(D);
        fence_regs(F);
      }
      Slot sk = take_a(c), k0 = sk, sv = sk;
      if (!lng) { k0 = take_a(c); sv = take_a(c); }
      tk = take_a(c);
      tv = tk;
      if (nblk > 1) tv = take_a(c);
      T6(c, 4);
      mbar_wait(c.sb + B_FULLG + k0.s * 8, k0.ph);
      WG_WAIT(0);
      fence_regs(S);
      T6(c, 5);
      c.release(px);
      c.release(sx);
      ok = mbar_test(c.sb + B_FULLG + tk.s * 8, tk.ph);
      bool qnow = QL == 0 || QL >= 4 || (QL == 2 && !lng) || (QL == 3 && lng);
      bool sok;
      if (qnow) sok = mbar_test(c.sb + B_STE + c.w * 8, (c.ph >> 10) & 1);
#pragma unroll
      for (int i = 0; i < 32; i++) P2[i] = pack_bf16(S[2 * i], S[2 * i + 1]);
      if (!lng) bar_sync(3 + c.w, 256);
      T6(c, 6);
      fence_regs(P2);
      auto qk64 = [&](float (&d)[32], uint32_t kbase, bool acc) {
        const uint64_t db = mkdesc(kbase, 16, 1024);
        WG_FENCE();
#pragma unroll
        for (int kk = 0; kk < 8; kk++)
          wgmma_rs_n64<0>(d, P2[4 * kk], P2[4 * kk + 1], P2[4 * kk + 2], P2[4 * kk + 3], db + (kk >> 2) * 1024 + (kk & 3) * 2, kk || acc);
        WG_COMMIT();
      };
      auto qk1 = [&] {
        WG_FENCE();
        qk_issue_r(S, P2, c.sb - A0 + tk.s * 32768);
        WG_COMMIT();
      };
      qk64(D, c.sb - A0 + k0.s * 32768 + odd * 8192, true);
      if (odd) qk64(F, c.sb - A0 + k0.s * 32768, false);
      else if (DF) WG_COMMIT();
      if (QL == 4) qnow = __all_sync(0xffffffffu, sok);
      if (QL == 6) qnow = c.pt == IT_AT;
      if (QL == 7) qnow = c.pt == IT_AT || __all_sync(0xffffffffu, sok);
      if (QL == 5) qnow = __all_sync(0xffffffffu, sok) || c.stage_free();
      if (QL == 9) qnow = c.pt == IT_AT;
      if (QL == 10) qnow = c.pt == IT_AT || lng;
      if (qnow || QL >= 9) {
#pragma unroll
        for (int i = 0; i < 32; i++)
          asm volatile("cvt.rn.bf16x2.f32 %0, %1, %2;" : "=r"(P[i]) : "f"(S[2 * i + 1]), "f"(S[2 * i]));
      }
      if (qnow) {
        if ((QL < 4 || QL > 5) && !sok) c.stage_wait();
        c.put_box(qbase, P);
        c.put_box(qbase, P + 16, 8192);
      }
      if (!ok) mbar_wait(c.sb + B_FULLG + tk.s * 8, tk.ph);
      qk1();
      bar_arrive(4 - c.w, 256);
      if (!lng) {
        mbar_wait(c.sb + B_FULLG + sk.s * 8, sk.ph);
        c.release(sk.s);
        mbar_wait(c.sb + B_FULLG + sv.s * 8, sv.ph);
        c.release(sv.s);
      }
      WG_WAIT(DF ? 2 : 1);
      fence_regs(D);
      if (!DF) fence_regs(F);
      T6(c, 7);
      if (!DF) c.release(k0.s);
      float x0 = fmaxf(D[0], D[1]), x1 = fmaxf(D[2], D[3]);
      auto rowmax = [&] {
#pragma unroll
        for (int b = 1; b < 8; b++) {
          x0 = fmaxf(x0, fmaxf(D[4 * b], D[4 * b + 1]));
          x1 = fmaxf(x1, fmaxf(D[4 * b + 2], D[4 * b + 3]));
        }
        if (odd) {
#pragma unroll
          for (int b = 0; b < 8; b++) {
            x0 = fmaxf(x0, fmaxf(F[4 * b], F[4 * b + 1]));
            x1 = fmaxf(x1, fmaxf(F[4 * b + 2], F[4 * b + 3]));
          }
        }
      };
#pragma unroll 1
      for (bool redo = true;; redo = false)
      {
        x0 = fmaxf(x0, __shfl_xor_sync(0xffffffffu, x0, 1));
        x1 = fmaxf(x1, __shfl_xor_sync(0xffffffffu, x1, 1));
        x0 = fmaxf(x0, __shfl_xor_sync(0xffffffffu, x0, 2));
        x1 = fmaxf(x1, __shfl_xor_sync(0xffffffffu, x1, 2));
        f.n0 = -x0 * CS; f.n1 = -x1 * CS;
        f.numer(D, P + 16, f.l0, f.l1, false);
        if (odd) f.numer(F, P, f.l0, f.l1, true);
        if (!redo || !__any_sync(0xffffffffu, fmaxf(f.l0, f.l1) > LAZY_SUM)) break;
        rowmax();
      }
      fence_regs(P);
      if (DF) c.release(k0.s);
      mbar_wait(c.sb + B_FULLG + tv.s * 8, tv.ph);
      if (qnow || QL >= 9) asm volatile("fence.proxy.async.shared::cta;" ::: "memory");
      WG_WAIT(0);
      fence_regs(S);
      fence_regs(P2);
      T6(c, 8);
      bar_sync(3 + c.w, 256);
      T6(c, 9);
      const uint64_t db = mkdesc(c.sb - A0 + tv.s * 32768, 16384, 1024);
      WG_FENCE();
#pragma unroll
      for (int kk = 0; kk < 4; kk++)
        wgmma_rs_n128<1>(O, P[16 + 4 * kk], P[17 + 4 * kk], P[18 + 4 * kk], P[19 + 4 * kk], db + odd * 512 + kk * 128, kk);
      WG_COMMIT();
      if (odd) {
        WG_FENCE();
#pragma unroll
        for (int kk = 0; kk < 4; kk++)
          wgmma_rs_n128<1>(O, P[4 * kk], P[4 * kk + 1], P[4 * kk + 2], P[4 * kk + 3], db + kk * 128, 1);
        WG_COMMIT();
      }
      bar_arrive(4 - c.w, 256);
      if (!qnow) {
        c.stage_wait();
        c.put_box(qbase, P2);
        c.put_box(qbase, P2 + 16, 8192);
        asm volatile("fence.proxy.async.shared::cta;" ::: "memory");
      }
    }
#pragma unroll 1
    for (int it = 1; it < nblk; it += 2) {
      attn_step<true>(c, S, O, P, P2, f, tk, tv, it + 1 < nblk, qbase, it > 1);
      if (it + 1 == nblk) break;
      attn_step<false>(c, S, O, P2, P, f, tk, tv, it + 2 < nblk, qbase, it > 1);
    }
    if (lng) {
      bar_sync(3 + c.w, 256);
      T6(c, 12);
      fence_regs(O);
      fence_regs(P2);
      WG_FENCE();
      pv_issue(O, P2, c.sb - A0 + tv.s * 32768);
      WG_COMMIT();
    } else if (nblk > 1) {
      bar_sync(3 + c.w, 256);
      T6(c, 12);
      fence_regs(O);
      fence_regs(P);
      WG_FENCE();
      pv_issue(O, P, c.sb - A0 + tv.s * 32768);
      WG_COMMIT();
      bar_arrive(4 - c.w, 256);
    }
    float l0 = f.l0, l1 = f.l1;
    l0 += __shfl_xor_sync(0xffffffffu, l0, 1);
    l1 += __shfl_xor_sync(0xffffffffu, l1, 1);
    l0 += __shfl_xor_sync(0xffffffffu, l0, 2);
    l1 += __shfl_xor_sync(0xffffffffu, l1, 2);
    float i0 = __fdividef(1.0f, l0), i1 = __fdividef(1.0f, l1);
    item = c.peek();
    asm volatile("" : "+f"(i0), "+f"(i1) :: "memory");
    const bool more = (item & 7) == IT_AT;
    if (more) {
      ok = false;
      fence_regs(S);
      px = chunk(Flag<true>());
      sx = chunk(Flag<false>());
      WG_WAIT(2);
    } else {
      WG_WAIT(0);
    }
    fence_regs(O);
    T6(c, 13);
    c.release(tv.s);
    ok = c.probe();
#pragma unroll
    for (int i = 0; i < 16; i++) {
      const int e = 32 + ((i >> 2) & 1) * 16 + (i >> 3) * 8 + (i & 3) * 2;
      pd[e] = pack_bf16(O[4 * i] * i0, O[4 * i + 1] * i0);
      pd[e + 1] = pack_bf16(O[4 * i + 2] * i1, O[4 * i + 3] * i1);
    }
#pragma unroll
    for (int i = 0; i < 32; i++) pd[i] = P[i];
    fence_regs(pd);
    ok = __all_sync(0xffffffffu, ok);
    c.pn = 2;
    c.pt = IT_AT;
    T6(c, 14);
    if (!more) break;
    T4(c);
    c.ia += 4;
    T6(c, 0);
  }
  WG_WAIT(0);
  c.pre = ok;
  return item;
}

struct Prod {
  uint32_t sb;
  uint32_t xchk;
  Ring r;
  __device__ __forceinline__ uint32_t acquire_g(uint32_t bytes, uint32_t drawn = 0) {
    const uint32_t s = r.gs;
    mbar_wait_nap(sb + B_EMPTYG + s * 8, (r.gph >> s) & 1);
    if (xchk) {
      xchk--;
      const uint32_t a0 = s + (s >> 1);
      mbar_wait_nap(sb + B_EMPTYA + a0 * 8, (r.aph >> a0) & 1);
      mbar_wait_nap(sb + B_EMPTYA + (a0 + 1) * 8, (r.aph >> (a0 + 1)) & 1);
    }
    r.gph ^= 1u << s;
    r.gs = (s + 1) & 3;
    asm volatile("st.shared.u32 [%0], %1;" ::"r"(sb + MISC_OFF + 32 + s * 8), "r"(drawn) : "memory");
    mbar_expect_tx(sb + B_FULLG + s * 8, bytes);
    PEV(1);
    return s;
  }
  __device__ __forceinline__ uint32_t acquire_a() {
    const uint32_t s = r.as;
    mbar_wait_nap(sb + B_EMPTYA + s * 8, (r.aph >> s) & 1);
    if (xchk) {
      xchk--;
      const uint32_t g0 = (0x322100u >> (s * 4)) & 3, g1 = (0x332110u >> (s * 4)) & 3;
      mbar_wait_nap(sb + B_EMPTYG + g0 * 8, (r.gph >> g0) & 1);
      mbar_wait_nap(sb + B_EMPTYG + g1 * 8, (r.gph >> g1) & 1);
    }
    r.aph ^= 1u << s;
    r.as = (s == 5) ? 0 : s + 1;
    mbar_expect_tx(sb + B_FULLA + s * 8, 32768);
    PEV(2);
    return s;
  }
};
__device__ __forceinline__ uint32_t wait_ready(uint32_t addr, uint32_t bits) {
  uint32_t v;
  asm volatile("ld.acquire.cta.shared::cta.u32 %0, [%1];" : "=r"(v) : "r"(addr) : "memory");
  if (!(v & bits)) {
    const uint32_t t0 = clk32();
    do {
      __nanosleep(20);
      spin_guard(t0);
      asm volatile("ld.acquire.cta.shared::cta.u32 %0, [%1];" : "=r"(v) : "r"(addr) : "memory");
    } while (!(v & bits));
  }
  return v;
}

__device__ __forceinline__ void ln_load(uint32_t dst, const bf16* src, uint32_t bar) {
  mbar_expect_tx(bar, 8192);
  asm volatile("cp.async.bulk.shared::cluster.global.mbarrier::complete_tx::bytes [%0], [%1], 8192, [%2];" ::"r"(dst), "l"(src), "r"(bar) : "memory");
}
__device__ __forceinline__ void bulk_store(void* dst, uint32_t src) {
  asm volatile("cp.async.bulk.global.shared::cta.bulk_group [%0], [%1], 8192;" ::"l"(dst), "r"(src) : "memory");
}
__device__ __forceinline__ uint4 lds128(uint32_t a) {
  uint4 v;
  asm volatile("ld.shared.v4.u32 {%0, %1, %2, %3}, [%4];" : "=r"(v.x), "=r"(v.y), "=r"(v.z), "=r"(v.w) : "r"(a) : "memory");
  return v;
}
__device__ __forceinline__ void stg128(void* p, const uint4& v) {
  asm volatile("st.global.v4.u32 [%0], {%1, %2, %3, %4};" ::"l"(p), "r"(v.x), "r"(v.y), "r"(v.z), "r"(v.w) : "memory");
}
__device__ __forceinline__ void layer_norm(const Params& p, uint32_t sb, uint32_t stg, uint32_t bar, uint32_t w, uint32_t lane) {
  const uint32_t a0 = stg + (lane >> 2) * 1024 + (lane & 7) * 16;
  uint32_t ph = 0;
#pragma unroll 1
  for (int rb = blockIdx.x; rb < 128; rb += gridDim.x) {
    const uint32_t ae = a0 + 1024;
    const size_t o = (size_t)(rb * 16 + w * 8) * DM;
    if (lane == 0) ln_load(stg, p.x + o, bar);
    ST(2);
    mbar_wait(bar, ph);
    ST(1);
    ph ^= 1;
    if (lane == 0) bulk_store(p.out + o, stg);
    uint32_t x0;
    asm volatile("ld.shared.u16 %0, [%1];" : "=r"(x0) : "r"(a0 & ~1023u) : "memory");
    const float sh = bf_lo(x0);
    float s0 = 0.f, s1 = 0.f, q0 = 0.f, q1 = 0.f;
#pragma unroll 1
    for (uint32_t a = a0; a < ae; a += 256) {
      const uint4 v[4] = {lds128(a), lds128(a ^ 64), lds128(a + 128), lds128((a ^ 64) + 128)};
#pragma unroll
      for (int i = 0; i < 16; i++) {
        const uint32_t u = ((const uint32_t*)v)[i];
        const float d0 = bf_lo(u) - sh, d1 = bf_hi(u) - sh;
        s0 += d0; s1 += d1;
        q0 = fmaf(d0, d0, q0); q1 = fmaf(d1, d1, q1);
      }
    }
    s0 += s1; q0 += q1;
    ST(4);
#pragma unroll
    for (int m = 1; m < 4; m <<= 1) {
      s0 += __shfl_xor_sync(0xffffffffu, s0, m);
      q0 += __shfl_xor_sync(0xffffffffu, q0, m);
    }
    s0 *= 1.0f / DM;
    const float var = fmaxf(fmaf(-s0, s0, q0 * (1.0f / DM)), 0.f);
    const uint32_t mb = pack_bf16(sh + s0, sh + s0);
    const float rden = 1.0f / round_bf16(sqrtf(round_bf16(round_bf16(var) + 1e-5f)));
    ST(6);
#pragma unroll 1
    for (uint32_t a = a0; a < ae; a += 256) {
      uint4 v[4] = {lds128(a), lds128(a ^ 64), lds128(a + 128), lds128((a ^ 64) + 128)};
#pragma unroll
      for (int i = 0; i < 16; i++) {
        uint32_t& u = ((uint32_t*)v)[i];
        asm("sub.rn.bf16x2 %0, %0, %1;" : "+r"(u) : "r"(mb));
        u = pack_bf16(bf_lo(u) * rden, bf_hi(u) * rden);
      }
#pragma unroll
      for (int i = 0; i < 4; i++)
        asm volatile("st.shared.v4.u32 [%0], {%1, %2, %3, %4};" ::"r"(((i & 1) ? a ^ 64 : a) + (i >> 1) * 128 + 8192), "r"(v[i].x), "r"(v[i].y), "r"(v[i].z), "r"(v[i].w) : "memory");
    }
    asm volatile("fence.proxy.async.shared::cta;" ::: "memory");
    __syncwarp();
    ST(7);
    if (lane == 0) {
      bulk_store(p.xn + o, stg + 8192);
      asm volatile("cp.async.bulk.commit_group;\ncp.async.bulk.wait_group 0;" ::: "memory");
      if (FASTW) red_relaxed(&p.flags[F_LN + (rb >> 3)]);
      else red_release(&p.flags[F_LN + (rb >> 3)]);
    }
    __syncwarp();
  }
}

__global__ void __cluster_dims__(2, 1, 1) __launch_bounds__(NTHREADS, 1)
mega_kernel(const __grid_constant__ Params p) {
  extern __shared__ uint8_t smem_raw[];
  const uint32_t sb = (smem_u32(smem_raw) + 1023) & ~1023u;
  const uint32_t tid = threadIdx.x, lane = tid & 31;
  const uint32_t warp = __shfl_sync(0xffffffffu, tid >> 5, 0);
  uint32_t rank;
  asm volatile("mov.u32 %0, %%cluster_ctarank;" : "=r"(rank));
  uint32_t cl = blockIdx.x >> 1;
  const int row0 = ((~cl & 7) * 2 + rank) * 128, grp0 = (cl >> 3) * 2;
  if (warp >= 6) {
    if (elect_one()) {
      const uint32_t b = sb + B_FULLG + (warp - 6) * 40 - (warp == 11 ? 8 : 0), cnt = warp < 8 || warp == 11 ? 1 : warp < 10 ? 16 : 4;
      mbar_init(b, cnt);
      if (warp == 6) {
        asm volatile("fence.proxy.async.shared::cta;" ::: "memory");
        mbar_expect_tx(b, 49152);
        if (ORD == 1) tma_load_2d(sb, &p.tm[TM_CKV], b, 0, row0);
        tma_load_3d(sb + 32768, &p.tm[TM_WUV], b, 0, 0, grp0);
        if (ORD == 0) tma_load_2d(sb, &p.tm[TM_CKV], b, 0, row0);
        tma_load_3d(sb + 16384, &p.tm[TM_WUK], b, 0, 0, grp0);
        if (ORD == 2) tma_load_2d(sb, &p.tm[TM_CKV], b, 0, row0);
      }
      mbar_init(b + 8, cnt);
      mbar_init(b + 16, warp == 11 ? 11 : cnt);
      mbar_init(b + 24, cnt);
      if (warp != 10) mbar_init(b + 32, cnt);
      asm volatile("fence.mbarrier_init.release.cluster;" ::: "memory");
    }
    __syncwarp();
  } else if (warp == 0) {
    asm volatile("st.shared.v4.u32 [%0], {%1, %1, %1, %1};" ::"r"(sb + RDY_OFF + lane * 16), "r"(0) : "memory");
    if (lane < 2) asm volatile("st.shared.v4.u32 [%0], {%1, %1, %1, %1};" ::"r"(sb + MISC_OFF + lane * 16), "r"(0) : "memory");
    asm volatile("fence.acq_rel.cta;" ::: "memory");
    __syncwarp();
  }
  ST(0);
  asm volatile("barrier.cluster.arrive.relaxed.aligned;" ::: "memory");
  if (warp == 0) {
    asm volatile("barrier.cluster.wait.aligned;" ::: "memory");
    ST(4);
    if (elect_one()) {
#pragma unroll
      for (int ks = 1; ks < 4; ks++) {
        if (DLY && ks >= 2) { const uint32_t t0 = clk32(); while (clk32() - t0 < DLY) ; }
        const uint32_t bar = sb + B_FULLG + ks * 8;
        mbar_expect_tx(bar, 49152);
        tma_load_3d_mc(sb + ks * 49152 + 16384 + rank * 16384, &p.tm[TM_WUK + rank], bar, 0, ks * 64, grp0, 0);
        tma_load_2d(sb + ks * 49152, &p.tm[TM_CKV], bar, ks * 64, row0);
      }
    }
    __syncwarp();
    ST(1);
  }
  asm volatile("" : "+r"(cl) :: "memory");
  const int i_beg = p.off[cl], i_end = p.off[cl + 1];
  if ((warp & 14) == 4) {
    const int n = i_beg + tid - 128;
    asm volatile("st.shared.u32 [%0], %1;" ::"r"(sb + ITEM_OFF + (tid - 128) * 4), "r"(n < i_end ? p.items[n] : (uint32_t)IT_END) : "memory");
  }

  if (warp < 4) {
    asm volatile("setmaxnreg.dec.sync.aligned.u32 40;");
    ST(5);
    if (warp == 0) {
      Prod pr;
      pr.sb = sb;
      pr.r.gs = 0; pr.r.as = 0; pr.r.gph = 0; pr.r.aph = 0x3f; pr.r.mode = 0; pr.xchk = 0;
      if (elect_one()) {
        for (int n = i_beg; n < i_end; n++) {
          const uint32_t item = p.items[n];
          const int type = item & 7, j = (item >> 3) & 7, idx = (item >> 6) & 31;
          const int k0 = (item >> 11) & 63, nk = (item >> 17) & 127;
          const uint32_t ra = sb + RDY_OFF + (n - i_beg) * 8;
          asm volatile("st.volatile.shared.u32 [%0], %1;" ::"r"(sb + MISC_OFF + 16), "r"(n) : "memory");
          uint32_t rdy = type <= IT_GU ? 0xffffffffu : 0u;
          auto need = [&](int b) {
            if (!((rdy >> b) & 1)) { T5(n - i_beg, 9); rdy = wait_ready(ra, 1u << b); T5(n - i_beg, 8); }
          };
          if (type != IT_AT) {
            if (pr.r.mode) pr.xchk = 4;
            pr.r.to_g();
            const CUtensorMap* ta = &p.tm[type == IT_KV ? TM_CKV : type == IT_GU ? TM_XN : type == IT_DN ? TM_H : TM_CTX];
            const CUtensorMap* tb = &p.tm[type == IT_KV ? TM_WUK + rank : type == IT_GU ? TM_WG + rank : type == IT_DN ? TM_WD : TM_WO];
            const int grp = (type <= IT_GU) ? idx * 2 : idx * 4 + (rank ^ ((item >> 28) & 1)) * 2;
            const int arow = (2 * j + rank) * 128;
            if (type == IT_GU) wait_ready(ra + 4, 1);
            const int sh = (item >> 25) & 7;
            int ke = k0 + nk, kp = 64, kl = 0;
            for (int i = 0; i < sh; i++) {
              const int e = (p.ends[sh] >> (i * 4)) & 15;
              kp -= e;
              if (i * 3 == k0) { ke = k0 + 3 + e; kl = kp - k0 - 3; }
            }
            uint32_t mail = sb + RDY_OFF + 256;
            int ta_ = 0, tb_ = 0;
            for (int q = n == i_beg ? 4 : k0; q < ke; q++) {
              int ks = q;
              if (sh && q > k0) {
                if (q >= k0 + 3) ks = q + kl;
                if (q <= k0 + 3) {
                  if (rank && q == k0 + 3) {
                    ta_ = wait_ready(mail, 256);
                    mail += 4;
                  }
                  if (ta_ < 256 + kp) {
                    if (q == k0 + 3) { ks = ta_ & 63; q--; }
                    if (rank == 0) {
                      int ep, v;
                      asm volatile("ld.shared.u32 %0, [%1];" : "=r"(ep) : "r"(sb + MISC_OFF + 20) : "memory");
                      asm volatile("atom.relaxed.gpu.global.add.u32 %0, [%1], 1;" : "=r"(v) : "l"(&p.flags[F_DYN + (j * 2 + idx) * 8]) : "memory");
                      if (q > k0 + 1) {
                        ta_ = tb_ + 256 + sh * 3 - ep * (kp - sh);
                        asm volatile("{\n.reg .b32 ra;\nmapa.shared::cluster.u32 ra, %0, 1;\nst.volatile.shared::cluster.u32 [ra], %1;\n}" ::"r"(mail), "r"(ta_) : "memory");
                        mail += 4;
                      }
                      tb_ = v;
                    }
                  }
                }
              }
              const uint32_t drawn = q < ke - 3;
              uint32_t s = pr.acquire_g(49152, drawn);
              if (n == i_beg && ks == 0) ST(6);
              if (n == i_beg && ks == 3) ST(7);
              uint32_t bar = sb + B_FULLG + s * 8;
              tma_load_3d_mc(sb + s * 49152 + 16384 + rank * 16384, tb, bar, 0, ks * 64, grp, (item & 0x10000002u) == 0x10000000u);
              need(ks >> 1);
              tma_load_2d(sb + s * 49152, ta, bar, ks * 64, arow);
            }
            if (type == IT_OP) pr.acquire_g(0);
          } else {
            if (!pr.r.mode) pr.xchk = 6;
            pr.r.to_a();
            wait_ready(ra + 4, 1);
            asm volatile("ld.acquire.cta.shared::cta.u32 %0, [%1];" : "=r"(rdy) : "r"(ra) : "memory");
            for (int ch = 0; ch < 8; ch++) {
              const uint32_t s = pr.acquire_a();
              const uint32_t bar = sb + B_FULLA + s * 8;
              tma_load_2d_mc(sb + s * 32768 + 16384 + rank * 8192, &p.tm[TM_WQ], bar, idx * 128 + rank * 64, ch * 64, item & (1 << 19));
              tma_load_3d(sb + s * 32768, &p.tm[TM_XQ + rank], bar, ch * 64, j * 256 + rank * 64, 0);
            }
            const int nb = 2 * j + 2;
            const int kc = (idx >= (int)p.ends[0] ? idx - 16 : idx) * 256 + rank * 64;
            for (int i = 0; i <= nb; i++) {
              if (i < nb) {
                if (NEED1) need(nb - 1 - i);
                uint32_t s = pr.acquire_a();
                if (!NEED1) need(nb - 1 - i);
                tma_load_2d_mc(sb + s * 32768 + rank * 16384, &p.tm[TM_KVL], sb + B_FULLA + s * 8, kc, (nb - 1 - i) * 128, (item >> ((nb - 1 - i) >> 1)) & 2048);
                }
              if (i > 0) {
                uint32_t s = pr.acquire_a();
                tma_load_2d_mc(sb + s * 32768 + rank * 16384, &p.tm[TM_KVL], sb + B_FULLA + s * 8, kc + 128, (nb - i) * 128, (item >> ((nb - i) >> 1)) & 2048);
                }
            }
          }
        }
        mbar_arrive(sb + B_DONE);
      }
      __syncwarp();
    } else {
      unsigned ep1 = 0;
      if (warp == 3) ep1 = ld_relaxed(&p.flags[F_EPOCH]) + 1;
      if (warp < 3) {
        const uint32_t w = warp - 1;
        const uint32_t stg = sb + STG_OFF + w * 16384;
        asm volatile("barrier.cluster.wait.aligned;" ::: "memory");
        if (LND) mbar_wait(sb + B_FULLG + (LND - 1) * 8, 0);
        layer_norm(p, sb, stg, sb + B_LN + w * 8, w, lane);
        ST(3);
        if (elect_one()) {
          mbar_arrive(sb + B_STE + w * 8);
          uint32_t stc = 0, opc = 0;
          for (int n = i_beg; n < i_end; n++) {
            const uint32_t item = p.items[n];
            const int type = item & 7, j = (item >> 3) & 7, idx = (item >> 6) & 31;
            const int mt = 2 * j + rank;
            int row = mt * 128 + w * 64;
            const CUtensorMap* tm = &p.tm[TM_KVS + type];
            const bool keep = n + 1 < i_end && (p.items[n + 1] & 7) == IT_OP;
            if (type == IT_OP) {
              wait_ready(sb + RDY_OFF + (n - i_beg) * 8 + 4, 1);
              for (int h = 0; h < 256; h += 128) {
                mbar_expect_tx(sb + B_STE + w * 8, 16384);
                const int gc = idx * 256 + (h ^ (item >> 28) * 128);
                tma_load_2d(stg, &p.tm[TM_GL], sb + B_STE + w * 8, gc, row);
                tma_load_2d(stg + 8192, &p.tm[TM_GL], sb + B_STE + w * 8, gc + 64, row);
                mbar_wait_st(sb + B_STF + w * 8, stc & 1);
                stc++;
              }
              if (!keep) mbar_arrive(sb + B_STE + w * 8);
              continue;
              if (FENCE_MODE) asm volatile("fence.proxy.async.shared::cta;" ::: "memory");
              tma_reduce_2d(tm, stg, idx * 256 + 128, row);
              tma_reduce_2d(tm, stg + 8192, idx * 256 + 192, row);
              asm volatile("cp.async.bulk.commit_group;" ::: "memory");
              mbar_wait(sb + B_ST2 + w * 8, opc & 1);
              opc++;
              uint32_t s1;
              asm volatile("ld.shared.u32 %0, [%1];" : "=r"(s1) : "r"(sb + MISC_OFF + w * 4) : "memory");
              const uint32_t rst = sb + s1 * 49152 + w * 8192;
              tma_reduce_2d(tm, rst, idx * 256, row);
              tma_reduce_2d(tm, rst + 16384, idx * 256 + 64, row);
              asm volatile("cp.async.bulk.commit_group;" ::: "memory");
              asm volatile("cp.async.bulk.wait_group.read 1;" ::: "memory");
              if (!keep) mbar_arrive(sb + B_STE + w * 8);
              asm volatile("cp.async.bulk.wait_group.read 0;" ::: "memory");
              mbar_arrive_cta4(sb + B_EMPTYG + s1 * 8, 0);
              mbar_arrive_cta4(sb + B_EMPTYG + s1 * 8, 1);
              continue;
            }
            unsigned* fp = &p.flags[type == IT_KV ? F_KV + idx * 16 + mt : type == IT_GU ? F_H + mt * 32 + idx : F_G + mt * 2 + idx];
            const bool wide = !(type & 1) && type != IT_AT;
            if (type == IT_AT) {
              const int g = (((item >> 24) & 1) == w) ? 3 - rank : rank;
              row = j * 256 + g * 64;
              fp = &p.flags[F_CTX + (2 * j + (g >> 1)) * 32 + idx];
            }
            int col = wide ? idx * 256 : idx * 128;
            if (type == IT_KV && idx >= (int)p.ends[0]) {
              col -= 16 * 256;
              wait_ready(sb + RDY_OFF + (n - i_beg) * 8 + 4, 1);
            }
            for (int r = wide; r >= 0; r--, col += 64) {
              mbar_wait_st(sb + B_STF + w * 8, stc & 1);
              T5(n - i_beg, w * 3);
              if (FENCE_MODE) asm volatile("fence.proxy.async.shared::cta;" ::: "memory");
              stc++;
#pragma unroll 1
              for (int q = 0; q < 128; q += SROWS) {
                tma_store_2d(tm, stg + q * 128, col + (q & 64) * (wide ? 2 : 1), row + (q & 63));
                asm volatile("cp.async.bulk.commit_group;" ::: "memory");
                asm volatile("{\n.reg .pred p;\nsetp.lt.u32 p, %0, 0x40000000;\n@p cp.async.bulk.wait_group.read 0;\n}" ::"r"(item) : "memory");
                if (SGAP) __nanosleep(SGAP);
              }
              asm volatile("cp.async.bulk.wait_group.read 0;" ::: "memory");
              if (r || !keep) mbar_arrive(sb + B_STE + w * 8);
            }
            asm volatile("cp.async.bulk.wait_group 0;" ::: "memory");
            T5(n - i_beg, w * 3 + 1);
            if (FASTW) red_relaxed(fp);
            else red_release(fp);
            T5(n - i_beg, w * 3 + 2);
          }
          mbar_arrive(sb + B_DONE);
        }
      } else {
        asm volatile("barrier.cluster.wait.aligned;" ::: "memory");
        if (TMP == 2) mbar_wait(sb + B_FULLG, 0);
        if (TMP && lane < TM_COUNT) asm volatile("prefetch.tensormap [%0];" ::"l"(&p.tm[lane]) : "memory");
        if (lane == 0) {
          asm volatile("st.shared.u32 [%0], %1;" ::"r"(sb + MISC_OFF + 20), "r"(ep1 - 1) : "memory");
          if (ep1) red_relaxed(&p.flags[F_START]);
          else red_release(&p.flags[F_START]);
          if (blockIdx.x == 0) {
            wait_flag(&p.flags[F_START], ep1 * gridDim.x);
            asm volatile("st.relaxed.gpu.global.u32 [%0], %1;" ::"l"(&p.flags[F_EPOCH]), "r"(ep1) : "memory");
          }
        }
        ep1 = __shfl_sync(0xffffffffu, ep1, 0);
        for (int n = i_beg; n <= i_end; n++) {
          const uint32_t item = n < i_end ? p.items[n] : (uint32_t)IT_END;
          const int type = item & 7, j = (item >> 3) & 7, idx = (item >> 6) & 31;
          const int k0 = (item >> 11) & 63, nk = (item >> 17) & 127;
          const unsigned* fb = &p.flags[type == IT_AT ? F_KV + idx * 16 : (type == IT_DN ? F_H : F_CTX) + (2 * j + rank) * 32] + lane;
          const int b0 = type == IT_AT ? 0 : k0 >> 1, b1 = type == IT_AT ? 2 * j + 1 : (k0 + nk - 1) >> 1;
          const bool skip = type <= IT_GU || (((int)lane < b0 || (int)lane > b1) && !((item >> 25) & 7));
          const unsigned* fx = &p.flags[type == IT_OP ? F_G + (2 * j + rank) * 2 + idx : type == IT_KV ? F_CTX + max((int)lane & 15, 2 * j) * 32 + (idx & 15) : F_LN + 2 * j + (lane & 1)];
          const unsigned tx = type == IT_OP || type == IT_KV ? ep1 * 2 : ep1 * 16;
          uint32_t m0 = 0, m1 = 0;
          if ((type == IT_KV && idx < (int)p.ends[0]) || type == IT_END) { m0 = 0xffffffffu; m1 = 1; }
          if (PFQ && type == IT_AT && lane < 8 && (PFQ == 3 || (PFQ == 2 ? (p.items[n - 1] & 7) != IT_AT : n <= i_beg + 3)))
            asm volatile("cp.async.bulk.prefetch.tensor.2d.L2.global.tile [%0, {%1, %2}];" ::"l"(&p.tm[TM_WQ]), "r"(idx * 128 + rank * 64), "r"(lane * 64) : "memory");
          const uint32_t t0 = clk32();
          while (true) {
            if (m0 != 0xffffffffu || !m1) {
              const unsigned va = ld_acquire(fb), vx = m1 ? tx : ld_acquire(fx);
              const uint32_t v0 = __ballot_sync(0xffffffffu, skip || (int)(va - ep1 * 2) >= 0);
              const uint32_t v1 = __all_sync(0xffffffffu, (int)(vx - tx) >= 0);
              if (v0 != m0 || v1 != m1) {
                m0 = v0; m1 = v1;
                T5(n - i_beg, 6);
                if (lane == 0) asm volatile("st.release.cta.shared::cta.v2.u32 [%0], {%1, %2};" ::"r"(sb + RDY_OFF + (n - i_beg) * 8), "r"(m0), "r"(m1) : "memory");
                T5(n - i_beg, 7);
              }
            }
            uint32_t cur;
            asm volatile("ld.volatile.shared.u32 %0, [%1];" : "=r"(cur) : "r"(sb + MISC_OFF + 16) : "memory");
            if (type == IT_END ? mbar_try(sb + B_DONE, 0) : m0 == 0xffffffffu && m1 && (int)cur >= n) break;
            __nanosleep(DEP_NAP);
            spin_guard(t0);
          }
        }
        if (lane == 0) {
        }
      }
      __syncwarp();
    }
    cluster_sync();
  } else {
    asm volatile("setmaxnreg.inc.sync.aligned.u32 232;");
    ST(5);
    Cons c;
    c.sb = sb; c.lane = lane; c.wi = warp & 3; c.w = (warp >> 2) - 1;
    c.s = 0; c.ph = 0; c.ia = sb + ITEM_OFF - 4;
    if (PV & 4) asm volatile("" : "+r"(c.sb));
    if (PV & 1) asm volatile("" : "+r"(c.ia));
    if (PV & 2) asm volatile("" : "+r"(c.w));
    if (PV & 8) asm volatile("" : "+r"(c.wi));
    if (PV & 16) asm volatile("" : "+r"(rank));
    if (PV & 32) asm volatile("" : "+r"(c.lane));
    if (PV & 64) asm volatile("" : "+r"(c.ph));
    if (PV & 128) asm volatile("" : "+r"(c.s));
    asm volatile("barrier.cluster.wait.aligned;" ::: "memory");
    ST(4);
    bar_sync(1, 256);
    uint32_t pd[64];
#pragma unroll
    for (int i = 0; i < 64; i++) pd[i] = 0;
    c.pn = 0; c.pt = 0;
    EV(c, 27);
    c.pre = false;
    for (uint32_t item = c.peek();;) {
      c.ia += 4;
      if ((item & 7) != IT_AT && !c.pre) {
        flush_some(c, pd, [&] { return item != IT_END && c.full_g(c.s) && c.full_g((c.s + 1) & 3); }, true);
        if (item == IT_END) break;
      }
      if ((item & 7) == IT_AT) item = attn_item(c, item, rank, pd);
      else item = gemm_item(c, item, rank, &p.tm[TM_OUTS], pd);
      T4(c);
    }
    EV(c, 63);
    if (lane == 0) mbar_arrive(sb + B_DONE);
    cluster_sync();
  }
}

typedef CUresult (*EncFn)(CUtensorMap*, CUtensorMapDataType, cuuint32_t, void*, const cuuint64_t*, const cuuint64_t*,
                          const cuuint32_t*, const cuuint32_t*, CUtensorMapInterleave, CUtensorMapSwizzle,
                          CUtensorMapL2promotion, CUtensorMapFloatOOBfill);

static void enc2d(EncFn enc, CUtensorMap* m, const void* ptr, uint64_t cols, uint64_t rows, uint32_t bc, uint32_t br) {
  cuuint64_t gd[2] = {cols, rows};
  cuuint64_t gs[1] = {cols * 2};
  cuuint32_t bd[2] = {bc, br}, es[2] = {1, 1};
  enc(m, CU_TENSOR_MAP_DATA_TYPE_BFLOAT16, 2, (void*)ptr, gd, gs, bd, es, CU_TENSOR_MAP_INTERLEAVE_NONE,
      CU_TENSOR_MAP_SWIZZLE_128B, CU_TENSOR_MAP_L2_PROMOTION_L2_256B, CU_TENSOR_MAP_FLOAT_OOB_FILL_NONE);
}
static void encq(EncFn enc, CUtensorMap* m, const void* ptr, uint64_t gap) {
  cuuint64_t gd[3] = {512, (cuuint64_t)SEQ - gap, 2};
  cuuint64_t gs[2] = {1024, gap * 1024};
  cuuint32_t bd[3] = {64, 64, 2}, es[3] = {1, 1, 1};
  enc(m, CU_TENSOR_MAP_DATA_TYPE_BFLOAT16, 3, (void*)ptr, gd, gs, bd, es, CU_TENSOR_MAP_INTERLEAVE_NONE,
      CU_TENSOR_MAP_SWIZZLE_128B, CU_TENSOR_MAP_L2_PROMOTION_L2_256B, CU_TENSOR_MAP_FLOAT_OOB_FILL_NONE);
}
static void enc3d(EncFn enc, CUtensorMap* m, const void* ptr, uint64_t cols, uint64_t rows) {
  cuuint64_t gd[3] = {64, rows, cols / 64};
  cuuint64_t gs[2] = {cols * 2, 128};
  cuuint32_t bd[3] = {64, 64, 2}, es[3] = {1, 1, 1};
  enc(m, CU_TENSOR_MAP_DATA_TYPE_BFLOAT16, 3, (void*)ptr, gd, gs, bd, es, CU_TENSOR_MAP_INTERLEAVE_NONE,
      CU_TENSOR_MAP_SWIZZLE_128B, CU_TENSOR_MAP_L2_PROMOTION_L2_256B, CU_TENSOR_MAP_FLOAT_OOB_FILL_NONE);
}

static const uint16_t k_off66[67] = {0, 14, 25, 34, 44, 55, 65, 76, 85, 93, 104, 118, 135, 146, 158, 171, 182, 192, 200, 209, 222, 233, 249, 261, 273, 282, 290, 300, 310, 319, 331, 342, 355, 367, 379, 388, 399, 408, 417, 429, 437, 447, 460, 472, 482, 490, 505, 515, 523, 532, 549, 561, 571, 583, 592, 600, 609, 620, 628, 637, 646, 654, 663, 672, 686, 695, 706};
static const uint32_t k_items66[706] = {
  0x10100038, 0x100228, 0x20100011, 0x11c, 0x108198c, 0x100359, 0x1001a9, 0x1005f8, 0x100550, 0x1006a8, 0x100720, 0x10100339,
  0x187ec, 0x190c4813, 0x10100030, 0x10100220, 0x201001c1, 0x100099, 0x380042, 0x100448, 0x380022, 0x100698, 0x100710, 0xfea4,
  0x190c4863, 0x10100028, 0x100218, 0x20100041, 0x30234, 0x1100408, 0x1081b0c, 0x1fcac, 0x103fe74, 0x1b0c4843, 0x10100020, 0x100210,
  0x20100478, 0x1f8ac, 0x101c36c, 0x7fd3c, 0x10005c4, 0x684, 0x1000704, 0x90c302b, 0x10100018, 0x100208, 0x20100049, 0xe4,
  0x10001c4, 0x80244, 0x100fbe4, 0x51c, 0x1001d4c, 0x80604, 0x90c3063, 0x10100010, 0x100001, 0x3c174, 0x1100458, 0x11100400,
  0x1100518, 0x138006a, 0x1100688, 0x11007c8, 0x190c4853, 0x10100008, 0x100200, 0x7f83c, 0x100e324, 0x1005a0, 0x10100171, 0x100770,
  0x1007a0, 0x100790, 0x8764, 0x90c300b, 0x10100000, 0x10100278, 0x3f874, 0x10819cc, 0x80284, 0x11002a1, 0x138002a, 0x138003a,
  0x80c007b, 0x10100078, 0x100270, 0x1c, 0x10838d4, 0x364, 0x103fcb4, 0x7ff3c, 0x1b0c484b, 0x10100070, 0x100268, 0x20100051,
  0x1f92c, 0x10002d4, 0x38c, 0x1001c0c, 0x8048c, 0x1000554, 0x87a4, 0x180c1873, 0x10100068, 0x100260, 0x20100428, 0x84,
  0x10302f4, 0x1acc, 0x1100558, 0x11100139, 0x1100618, 0x111002b9, 0x11006c8, 0x1000644, 0x3f94, 0xa0c004b, 0x10100060, 0x100258,
  0x201001c9, 0x100311, 0x104, 0x1100069, 0x11004a0, 0x1100490, 0x11002e1, 0x1100031, 0x1100670, 0x11005c8, 0x1100640, 0x111006c0,
  0x11100780, 0x10006c4, 0x160c185b, 0x10100058, 0x100250, 0x20100081, 0x30274, 0x11000e9, 0x1100578, 0x11004c0, 0x111000f9, 0x1100231,
  0x10706bc, 0xa0c606b, 0x10100050, 0x100248, 0x20100089, 0xc4, 0x10782bc, 0x34c, 0x11000f1, 0x111001f9, 0x11006e0, 0x1000594,
  0x6d4, 0x190c483b, 0x10100048, 0x100240, 0x201004b8, 0x1f8ec, 0x1007a9c, 0x1004d0, 0x10100079, 0x1005d0, 0x1002f1, 0x1007d8,
  0x665c, 0x10807c4, 0x190c4873, 0x10100040, 0x1002b8, 0x4, 0x108008c, 0x7e2fc, 0x1100568, 0x1100638, 0x1100588, 0x107fe7c,
  0x80f44, 0x190c487b, 0x101000b8, 0x101002b0, 0x20100301, 0x100468, 0x380002, 0x38005a, 0x1007b8, 0x10100279, 0x38007a, 0x90c3033,
  0x101000b0, 0x1002a8, 0x3f8b4, 0x100fa64, 0x8464, 0x103e5f4, 0x81e8c, 0x180c1813, 0x101000a8, 0x1002a0, 0x7f87c, 0x101fb2c,
  0x80bc4, 0x1003c94, 0x5dc, 0x100471c, 0x180c1853, 0x101000a0, 0x100298, 0x201001d1, 0x1000d9, 0x38000a, 0x100169, 0x1005b8,
  0x10100039, 0x101001b9, 0x101005c0, 0x100371, 0x100748, 0x90c3073, 0x10100098, 0x100290, 0x5c, 0x1000184, 0x7fb7c, 0x1100508,
  0x1100668, 0x1100768, 0x1100758, 0x101872c, 0x90c303b, 0x10100090, 0x100288, 0x20100201, 0x100021, 0x1000a1, 0x100029, 0x1000a9,
  0x100129, 0x1001e9, 0x100329, 0x1001b1, 0x10100239, 0x101002f9, 0x10100379, 0x101007c0, 0x90c3013, 0x10100088, 0x100280, 0x20100091,
  0xcc, 0x101e22c, 0x1f42c, 0x11007f8, 0x1100600, 0x1100750, 0x11100740, 0x1000754, 0xb0c306b, 0x10100080, 0x1002f8, 0x20100209,
  0x100119, 0x38004a, 0x100530, 0x100520, 0x100071, 0x1006f8, 0x100728, 0x1fe2c, 0x80c003b, 0x101000f8, 0x101002f0, 0xc,
  0x107fa3c, 0x80ac4, 0x101fc6c, 0x30634, 0x1081f0c, 0x80c002b, 0x101000f0, 0x1002e8, 0x201000c1, 0x302b4, 0x10003a4, 0x1c4ec,
  0x107e7bc, 0x190c4803, 0x101000e8, 0x1002e0, 0x3c0f4, 0x100faa4, 0x3bd4, 0x11006b0, 0x11002b1, 0x1100331, 0x101ff6c, 0x190c4823,
  0x101000e0, 0x1002d8, 0x20100211, 0x100019, 0xc1e4, 0x101c3ec, 0x100179, 0x100271, 0x380072, 0x190c482b, 0x101000d8, 0x1002d0,
  0x24, 0x1030334, 0x3cc, 0x11006b8, 0x107fdfc, 0x806cc, 0x190c481b, 0x101000d0, 0x1002c8, 0x201000c9, 0x124, 0x1000214,
  0x304, 0x1100361, 0x1100131, 0x11006f0, 0x10005e4, 0x479c, 0x80c0003, 0x101000c8, 0x1002c0, 0x20100241, 0x100341, 0x619c,
  0x100031c, 0x414, 0x1000484, 0x504, 0x10706fc, 0x1b0c486b, 0x101000c0, 0x100338, 0x20100249, 0x100159, 0x380012, 0x1004e8,
  0x100321, 0x1005a8, 0x1001f1, 0x100658, 0x100718, 0x1feec, 0x90c3023, 0x10100138, 0x100330, 0x7f8bc, 0x1001a0c, 0x100261,
  0x100560, 0x10100500, 0x100778, 0x100610, 0x10100680, 0x10100700, 0x180c1803, 0x10100130, 0x10100328, 0x201000d1, 0x164, 0x10082e4,
  0x100510, 0x100598, 0x100620, 0x1007e8, 0x1006d0, 0x107ac, 0x1a0c184b, 0x10100128, 0x100320, 0x20100251, 0x100349, 0x1dc,
  0x107e43c, 0x7fdbc, 0x1007fdc, 0x190c480b, 0x10100120, 0x100318, 0x20100281, 0x1001d9, 0x100299, 0x1004a8, 0x7f3fc, 0x1038574,
  0x614, 0x10007cc, 0x80c0063, 0x10100118, 0x100310, 0x3c134, 0x103f374, 0x1000b1, 0x100738, 0x81ccc, 0x103fef4, 0x80c0053,
  0x10100110, 0x100308, 0x20100101, 0x15c, 0x10783bc, 0x449c, 0x108050c, 0x61c, 0x60c005b, 0x10100108, 0x100300, 0x20100470,
  0x80014, 0x101fa6c, 0x10100480, 0x100369, 0x100590, 0x1007b0, 0x1007e0, 0x30774, 0x80c0033, 0x10100100, 0x10100378, 0x44,
  0x10301f4, 0x1fbac, 0x107fd7c, 0xff24, 0xb0c3043, 0x10100178, 0x100370, 0x20100109, 0x10c, 0x1083954, 0x303f4, 0x101fd2c,
  0x80584, 0x1007e9c, 0x180c1863, 0x10100170, 0x100368, 0x3f834, 0x1100410, 0x1100498, 0x1100488, 0x11005b0, 0x1100678, 0x11100540,
  0x11007a8, 0x1100798, 0x1100788, 0x180c180b, 0x10100168, 0x100360, 0x1f82c, 0x10039d4, 0x100221, 0x100229, 0x101004c8, 0x1005d8,
  0x1007f0, 0x100690, 0x3ffb4, 0xa0c006b, 0x10100160, 0x100358, 0x20100111, 0x1f96c, 0x100028c, 0x100528, 0x100269, 0x4e4,
  0x101066c, 0xb0c304b, 0x10100158, 0x100350, 0x7f8fc, 0x1003a54, 0x41c, 0x10004dc, 0x7f77c, 0x1a0c186b, 0x10100150, 0x100348,
  0x20100289, 0x100061, 0x100259, 0x100121, 0x1001a1, 0x100450, 0x10100440, 0x1002e9, 0x100630, 0x100660, 0x100760, 0xfe24,
  0x80c0023, 0x10100148, 0x100340, 0x7f93c, 0x100024c, 0x3b54, 0x1007c5c, 0x655c, 0x100060c, 0x74c, 0x80c000b, 0x10100140,
  0x1003b8, 0x20100141, 0x1a4, 0x101faec, 0x3e4f4, 0x103e6b4, 0x180c183b, 0x101001b8, 0x1003b0, 0x9c, 0x1083914, 0x294,
  0x103fc74, 0x1c5ec, 0x1002714, 0x90c3053, 0x101001b0, 0x1003a8, 0x20100291, 0x100219, 0x1000e1, 0x1002d9, 0x100460, 0x1004f8,
  0x1004e0, 0x1002a9, 0x1005e8, 0x100730, 0x100650, 0x80544, 0x1081dcc, 0x3fd4, 0x80c0073, 0x101001a8, 0x101003a0, 0x20100149,
  0x8f864, 0x1100319, 0x11004f0, 0x1003394, 0x1005e0, 0x10100580, 0x10100608, 0x30734, 0x80c0013, 0x101001a0, 0x100398, 0x20100420,
  0xdc, 0x100025c, 0x3dc, 0x100044c, 0x514, 0x100058c, 0x180c181b, 0x10100198, 0x100390, 0x20100151, 0xa4, 0x1100161,
  0x11001e1, 0x1100570, 0x1380062, 0x11100648, 0x1100708, 0x10006dc, 0xa0c0043, 0x10100190, 0x100388, 0x4c, 0x107c27c, 0x439c,
  0x111000b9, 0x10005a4, 0xfee4, 0xa0c6043, 0x10100188, 0x100380, 0x20100181, 0x7e1fc, 0x107047c, 0x1fdac, 0x1007f5c, 0x1a0c1843,
  0x10100180, 0x101003f8, 0x201002c1, 0x100351, 0x1f9ec, 0x10784bc, 0x7fe3c, 0x1001f8c, 0x190c4833, 0x101001f8, 0x1003f0, 0x201002c9,
  0x100059, 0x144, 0x107fb3c, 0x454, 0x10004c4, 0x59c, 0x1000694, 0x180c187b, 0x101001f0, 0x1003e8, 0x1006c, 0x101faac,
  0x80b44, 0x1030534, 0x186ac, 0x180c182b, 0x101001e8, 0x1003e0, 0x201004b0, 0x54, 0x100021c, 0x314, 0x107fcfc, 0x7fffc,
  0x90c301b, 0x101001e0, 0x100009, 0x100309, 0x14c, 0x100fa24, 0x424, 0x100fd24, 0x307f4, 0xa0c604b, 0x101001d8, 0x1003d8,
  0x7f97c, 0x1080204, 0x3fc34, 0x1000564, 0x3dd4, 0x70c305b, 0x101001d0, 0x1003d0, 0x20100418, 0x3f9b4, 0x138001a, 0x1100548,
  0x11006a0, 0x1380032, 0x180c1833, 0x101001c8, 0x1003c8, 0x20100189, 0x181ac, 0x103fbb4, 0x80c04, 0x103fdb4, 0x81e4c, 0x180c1823,
  0x101001c0, 0x1003c0, 0x201002d1, 0x100199, 0x380052, 0x100538, 0x1004d8, 0x1005f0, 0x100628, 0x1006e8, 0x1006d8, 0x1007d0,
  0xc7e4, 0x90c3003, 0x100238, 0x100438, 0x7c1bc, 0x10072dc, 0x4a4, 0x1003cd4, 0x8664, 0x1080784, 0x80c001b, 0x100230,
  0x100430, 0x20100191, 0x94, 0x1003994, 0x35c, 0x1080b84, 0x80444, 0x101fd6c, 0x654, 0x90c307b,
};
struct SItem { int type, j, idx, k0, nk; float cost, prio, done; };
struct SchedCfg {
  int ops[8];
  float c_kv, c_gu, c_at0, c_atb, c_ks, c_epi, lat;
  float p_gu, p_dn, p_op;
};
static SchedCfg g_cfg = {{4, 4, 4, 4, 4, 4, 4, 4}, 6.3f, 6.7f, 6.9f, 1.42f, 0.63f, 1.2f, 3.0f, 33.f, 60.f, 0.f};

static float build_schedule(Params& P, int ncl) {
  static SItem it[MAX_ITEMS];
  const SchedCfg& C = g_cfg;
  int n = 0;
  auto add = [&](int type, int j, int idx, int k0, int nk, float cost, float prio) {
    it[n].type = type; it[n].j = j; it[n].idx = idx; it[n].k0 = k0; it[n].nk = nk;
    it[n].cost = cost; it[n].prio = prio; it[n].done = -1; n++;
  };
  const int kv0 = n;
  for (int h = 0; h < 32; h++) for (int j = 7; j >= 0; j--) add(IT_KV, j, h, 0, 8, C.c_kv, 100.f - 0.01f * h);
  const int gu0 = n;
  for (int j = 0; j < 8; j++) for (int f = 0; f < 14; f++) add(IT_GU, j, f, 0, 8, C.c_gu, C.p_gu + 0.01f * j);
  const int at0 = n;
  for (int j = 0; j < 8; j++) for (int h = 0; h < 32; h++) add(IT_AT, j, h, 0, 0, C.c_at0 + 2 * j * C.c_atb, 20.f + 2.9f * j - 0.01f * h);
  const int dn0 = n;
  for (int j = 0; j < 8; j++) for (int c = 0; c < 2; c++) add(IT_DN, j, c, 0, 28, 28 * C.c_ks + C.c_epi, C.p_dn);
  for (int j = 0; j < 8; j++) for (int s = 0; s < C.ops[j]; s++) for (int c = 0; c < 2; c++)
    add(IT_OP, j, c, s * (64 / C.ops[j]), 64 / C.ops[j], (64 / C.ops[j]) * C.c_ks + C.c_epi, C.p_op + 0.01f * j);
  auto ready = [&](int i) -> float {
    float t = 0;
    auto dep = [&](int d) { if (t >= 0) { if (it[d].done < 0) t = -1; else if (it[d].done + C.lat > t) t = it[d].done + C.lat; } };
    const SItem& a = it[i];
    if (a.type == IT_GU) t = 4.0f;
    else if (a.type == IT_DN) { for (int f = 0; f < 14; f++) dep(gu0 + a.j * 14 + f); }
    else if (a.type == IT_AT) { for (int j = 0; j <= a.j; j++) dep(kv0 + a.idx * 8 + 7 - j); if (t > 3.5f) t -= 3.5f; }
    else if (a.type == IT_OP) { dep(dn0 + a.j * 2 + a.idx); for (int h = a.k0 / 2; h <= (a.k0 + a.nk - 1) / 2; h++) dep(at0 + a.j * 32 + h); }
    return t;
  };
  static int list[MAX_CL][64];
  int cnt[MAX_CL];
  float tfree[MAX_CL];
  for (int c = 0; c < ncl; c++) { cnt[c] = 0; tfree[c] = 2.0f; }
  float span = 0;
  for (int left = n; left > 0; left--) {
    int c = 0;
    for (int k = 1; k < ncl; k++) if (tfree[k] < tfree[c]) c = k;
    int best = -1, bw = -1;
    float bt = 1e30f;
    for (int i = 0; i < n; i++) {
      if (it[i].done >= 0) continue;
      const float r = ready(i);
      if (r < 0) continue;
      if (r <= tfree[c]) { if (best < 0 || it[i].prio > it[best].prio) best = i; }
      else if (r < bt) { bt = r; bw = i; }
    }
    if (best >= 0) bt = tfree[c]; else best = bw;
    tfree[c] = it[best].done = bt + it[best].cost;
    if (tfree[c] > span) span = tfree[c];
    list[c][cnt[c]++] = best;
  }
  int o = 0;
  for (int c = 0; c < ncl; c++) {
    P.off[c] = (uint16_t)o;
    int lead = 0;
    for (int k = 0; k < cnt[c]; k++) {
      const SItem& a = it[list[c][k]];
      P.items[o++] = mk_item(a.type, a.j, a.idx, a.k0, a.nk, lead);
      if (a.type == IT_AT) lead ^= 1;
    }
  }
  P.off[ncl] = (uint16_t)o;
  return span;
}

}

extern "C" void kernel_launch(void* const* d_in, const int* in_sizes, int n_in, void* d_out, int out_size) {
  using namespace mk;
  static Params P;
  static int ncl = 0;
  static const void* cached[11];
  bool same = ncl > 0 && cached[10] == d_out;
  for (int i = 0; i < 10 && same; i++) same = cached[i] == d_in[i];
  if (!same) {
    void* fn = nullptr;
    cudaDriverEntryPointQueryResult qr;
    cudaGetDriverEntryPoint("cuTensorMapEncodeTiled", &fn, cudaEnableDefault, &qr);
    EncFn enc = (EncFn)fn;
    void *xn, *kv, *h, *ctx, *aux;
    cudaGetSymbolAddress(&xn, g_xn);
    cudaGetSymbolAddress(&kv, g_kv);
    cudaGetSymbolAddress(&h, g_h);
    cudaGetSymbolAddress(&ctx, g_ctx);
    cudaGetSymbolAddress(&aux, g_gate);
    enc2d(enc, &P.tm[TM_XN], xn, 512, SEQ, 64, 128);
    enc2d(enc, &P.tm[TM_CKV], d_in[1], 512, SEQ, 64, 128);
    enc2d(enc, &P.tm[TM_H], h, DFF, SEQ, 64, 128);
    enc2d(enc, &P.tm[TM_CTX], ctx, 4096, SEQ, 64, 128);
    enc3d(enc, &P.tm[TM_WUK], d_in[3], 4096, 512);
    enc3d(enc, &P.tm[TM_WUV], d_in[4], 4096, 512);
    enc3d(enc, &P.tm[TM_WG], d_in[7], DFF, 512);
    enc3d(enc, &P.tm[TM_WU], d_in[8], DFF, 512);
    enc3d(enc, &P.tm[TM_WD], d_in[9], 512, DFF);
    enc3d(enc, &P.tm[TM_WO], d_in[5], 512, 4096);
    enc2d(enc, &P.tm[TM_WQ], d_in[2], 4096, 512, 64, 64);
    enc2d(enc, &P.tm[TM_KVL], kv, 8192, SEQ, 64, 128);
    enc2d(enc, &P.tm[TM_KVS], kv, 8192, SEQ, 64, SROWS);
    enc2d(enc, &P.tm[TM_HS], h, DFF, SEQ, 64, SROWS);
    enc2d(enc, &P.tm[TM_CTXS], ctx, 4096, SEQ, 64, SROWS);
    enc2d(enc, &P.tm[TM_GS], aux, 512, SEQ, 64, SROWS);
    enc2d(enc, &P.tm[TM_GL], aux, 512, SEQ, 64, 64);
    encq(enc, &P.tm[TM_XQ], xn, 192);
    encq(enc, &P.tm[TM_XQ1], xn, 64);
    enc2d(enc, &P.tm[TM_OUTS], d_out, 512, SEQ, 64, WRED ? 16 : 64);
    const uint32_t ends[8] = {32, 3, 0x33, 0x333, 0x3333, 0x33333, 0x333333, 0x3333333};
    memcpy(P.ends, ends, sizeof(ends));
    P.x = (const bf16*)d_in[0];
    P.out = (bf16*)d_out;
    P.xn = (bf16*)xn;
    cudaGetSymbolAddress((void**)&P.flags, g_flags);
    cudaFuncSetAttribute(mega_kernel, cudaFuncAttributeMaxDynamicSharedMemorySize, SMEM_BYTES);
    if (ncl == 0) {
      cudaLaunchConfig_t cfg = {};
      cfg.gridDim = dim3(132); cfg.blockDim = dim3(NTHREADS); cfg.dynamicSmemBytes = SMEM_BYTES;
      cudaLaunchAttribute at[1];
      at[0].id = cudaLaunchAttributeClusterDimension;
      at[0].val.clusterDim.x = 2; at[0].val.clusterDim.y = 1; at[0].val.clusterDim.z = 1;
      cfg.attrs = at; cfg.numAttrs = 1;
      int nc = 0;
      if (cudaOccupancyMaxActiveClusters(&nc, mega_kernel, &cfg) != cudaSuccess || nc < 1) { nc = 66; (void)cudaGetLastError(); }
      if (nc > MAX_CL) nc = MAX_CL;
      if (nc < 16) nc = 16;
      ncl = nc;
      if (ncl == 66) {
        memcpy(P.off, k_off66, sizeof(k_off66));
        memcpy(P.items, k_items66, sizeof(k_items66));
      } else {
        build_schedule(P, ncl);
      }
    }
    for (int i = 0; i < 10; i++) cached[i] = d_in[i];
    cached[10] = d_out;
  }
  mega_kernel<<<ncl * 2, NTHREADS, SMEM_BYTES>>>(P);
}
```
